```python
import torch

def _softmax(x, axis=-1):
    return torch.softmax(x, dim=axis)
def _gelu(x):
    return torch.nn.functional.gelu(x, approximate="tanh")
def _silu(x):
    return torch.nn.functional.silu(x)
def _sigmoid(x):
    return torch.sigmoid(x)
def _layernorm(x, axis=-1, eps=1e-5):
    m = x.mean(dim=axis, keepdim=True)
    v = x.var(dim=axis, keepdim=True, unbiased=False)
    return (x - m) / torch.sqrt(v + eps)
def _scatter_add(tgt, idx, src, axis=0):
    return tgt.clone().index_add_(axis, idx, src)
def _segment_sum(src, seg, n):
    out = torch.zeros((n,) + src.shape[1:], dtype=src.dtype)
    return out.index_add_(0, seg, src)
def _pad(x, pw):
    flat = tuple(v for pair in reversed(pw) for v in pair)
    return torch.nn.functional.pad(x, flat)

kernel_name = 'standalone__gqa_block_cached__near_ridge'

def setup_inputs():

    _w = (lambda a: (lambda t: t.to(torch.bfloat16) if t.is_floating_point() else t)(torch.as_tensor(a)))
    B, Sq, D = 16, 112, 576
    Hq, Hkv, Sk, Dh = 32, 16, 512, 128
    assert Hq % Hkv == 0, (Hq, Hkv)
    return {
        "x": _w((lambda *s: torch.randn(*s, dtype=torch.bfloat16) * 0.8)(B, Sq, D)),
        "k_cache": _w((lambda *s: torch.randn(*s, dtype=torch.bfloat16) * 0.8)(B, Hkv, Sk, Dh)),
        "v_cache": _w((lambda *s: torch.randn(*s, dtype=torch.bfloat16) * 0.05)(B, Hkv, Sk, Dh)),
        "wq": _w((lambda *s: torch.randn(*s, dtype=torch.bfloat16) * 0.8)(D, Hq * Dh) * (D ** -0.5)),
        "wo": _w((lambda *s: torch.randn(*s, dtype=torch.bfloat16) * 0.05)(Hq * Dh, D) * ((Hq * Dh) ** -0.5)),
    }

def reference(x, k_cache, v_cache, wq, wo):
    B, Sq, D = x.shape
    Hq, Dh = 32, 128
    Hkv = k_cache.shape[1]
    rep = Hq // Hkv
    q = (lambda x, *d: x.permute(*d))((x @ wq).reshape(B, Sq, Hq, Dh), 0, 2, 1, 3)
    k = (lambda x, n, axis: torch.repeat_interleave(x, n, dim=axis))(k_cache, rep, axis=1)
    v = (lambda x, n, axis: torch.repeat_interleave(x, n, dim=axis))(v_cache, rep, axis=1)
    scores = torch.einsum("bhqd,bhkd->bhqk", q, k) * (Dh ** -0.5)
    p = _softmax(scores, axis=-1)
    o = torch.einsum("bhqk,bhkd->bhqd", p, v)
    return (lambda x, *d: x.permute(*d))(o, 0, 2, 1, 3).reshape(B, Sq, Hq * Dh) @ wo
```

```cpp
#include <cuda_runtime.h>
#include <cuda_bf16.h>
#include <cuda.h>
#include <stdint.h>

namespace {

constexpr int B_ = 16, SQ = 112, DM = 576, HQ = 32, HKV = 16, SK = 512, DH = 128;
constexpr int NSLOT = 6;
constexpr int SLOT_BYTES = 16384;
constexpr int BLK = 112 * 128;
constexpr int NFILL_Q = 36, NFILL_KV = 32, NFILL_O = 36;
constexpr int FILL_KV0 = NFILL_Q, FILL_O0 = NFILL_Q + NFILL_KV, NFILL = FILL_O0 + NFILL_O;
constexpr int OFF_SLOTS = 9 * BLK;
constexpr int OFF_BARS = OFF_SLOTS + NSLOT * SLOT_BYTES;
constexpr int NBARS = 2 * NFILL + 9;
constexpr int SMEM_BYTES = OFF_BARS + NBARS * 8 + 64;
constexpr int NTHREADS = 384;
constexpr uint32_t SPIN_LIMIT = 1u << 22;

__device__ uint4 g_part[B_ * 9 * 8 * 7 * 128];
__device__ uint32_t g_flag[B_ * 9 * 8];

#define TSTAMP(i) do {} while (0)

__device__ __forceinline__ uint32_t smem_u32(const void* p) { return (uint32_t)__cvta_generic_to_shared(p); }
__device__ __forceinline__ void mbar_init(uint32_t bar, uint32_t cnt) { asm volatile("mbarrier.init.shared::cta.b64 [%0], %1;" ::"r"(bar), "r"(cnt) : "memory"); }
__device__ __forceinline__ void mbar_expect_tx(uint32_t bar, uint32_t bytes) { asm volatile("mbarrier.arrive.expect_tx.shared::cta.b64 _, [%0], %1;" ::"r"(bar), "r"(bytes) : "memory"); }
__device__ __forceinline__ void mbar_arrive(uint32_t bar) { asm volatile("mbarrier.arrive.shared::cta.b64 _, [%0];" ::"r"(bar) : "memory"); }
__device__ __forceinline__ void mbar_arrive_remote(uint32_t rbar) { asm volatile("mbarrier.arrive.shared::cluster.b64 _, [%0];" ::"r"(rbar) : "memory"); }
__device__ __forceinline__ void mbar_wait(uint32_t bar) {
  uint32_t done, it = 0;
  do {
    asm volatile("{\n.reg .pred p;\nmbarrier.try_wait.parity.shared::cta.b64 p, [%1], 0;\nselp.u32 %0, 1, 0, p;\n}\n" : "=r"(done) : "r"(bar) : "memory");
    if (++it > SPIN_LIMIT) break;
  } while (!done);
}
__device__ __forceinline__ void mbar_wait_cluster(uint32_t bar) {
  uint32_t done, it = 0;
  do {
    asm volatile("{\n.reg .pred p;\nmbarrier.try_wait.parity.acquire.cluster.shared::cta.b64 p, [%1], 0;\nselp.u32 %0, 1, 0, p;\n}\n" : "=r"(done) : "r"(bar) : "memory");
    if (++it > SPIN_LIMIT) break;
  } while (!done);
}
__device__ __forceinline__ uint32_t mapa(uint32_t addr, uint32_t cta) { uint32_t r; asm volatile("mapa.shared::cluster.u32 %0, %1, %2;" : "=r"(r) : "r"(addr), "r"(cta)); return r; }
__device__ __forceinline__ void tma_2d(uint32_t dst, const CUtensorMap* m, int c0, int c1, uint32_t bar) {
  asm volatile("cp.async.bulk.tensor.2d.shared::cluster.global.mbarrier::complete_tx::bytes [%0], [%1, {%3, %4}], [%2];" ::"r"(dst), "l"(m), "r"(bar), "r"(c0), "r"(c1) : "memory");
}
__device__ __forceinline__ void tma_2d_mc(uint32_t dst, const CUtensorMap* m, int c0, int c1, uint32_t bar) {
  asm volatile("cp.async.bulk.tensor.2d.shared::cluster.global.mbarrier::complete_tx::bytes.multicast::cluster [%0], [%1, {%3, %4}], [%2], %5;" ::"r"(dst), "l"(m), "r"(bar), "r"(c0), "r"(c1), "h"((uint16_t)3) : "memory");
}
__device__ __forceinline__ void tma_3d(uint32_t dst, const CUtensorMap* m, int c0, int c1, int c2, uint32_t bar) {
  asm volatile("cp.async.bulk.tensor.3d.shared::cluster.global.mbarrier::complete_tx::bytes [%0], [%1, {%3, %4, %5}], [%2];" ::"r"(dst), "l"(m), "r"(bar), "r"(c0), "r"(c1), "r"(c2) : "memory");
}
__device__ __forceinline__ void tma_store_2d(const CUtensorMap* m, uint32_t src, int c0, int c1) {
  asm volatile("cp.async.bulk.tensor.2d.global.shared::cta.bulk_group [%0, {%2, %3}], [%1];" ::"l"(m), "r"(src), "r"(c0), "r"(c1) : "memory");
}
__device__ __forceinline__ void prefetch_tmap(const CUtensorMap* m) { asm volatile("prefetch.tensormap [%0];" ::"l"(m) : "memory"); }
__device__ __forceinline__ void named_bar(int id, int n) { asm volatile("bar.sync %0, %1;" ::"r"(id), "r"(n) : "memory"); }
__device__ __forceinline__ void fence_async_smem() { asm volatile("fence.proxy.async.shared::cta;" ::: "memory"); }
#define WG_FENCE() asm volatile("wgmma.fence.sync.aligned;" ::: "memory")
#define WG_COMMIT() asm volatile("wgmma.commit_group.sync.aligned;" ::: "memory")
#define WG_WAIT(n) asm volatile("wgmma.wait_group.sync.aligned %0;" ::"n"(n) : "memory")
template <int N> __device__ __forceinline__ void pin(float (&d)[N]) {
#pragma unroll
  for (int i = 0; i < N; i++) asm volatile("" : "+f"(d[i])::"memory");
}
__device__ __forceinline__ uint64_t mkdesc(uint32_t addr, uint32_t lbo16) {
  uint32_t lo = (addr >> 4) + (lbo16 << 16);
  uint32_t hi = 64u | (1u << 30);
  return ((uint64_t)hi << 32) | lo;
}
__device__ __forceinline__ uint32_t pack_bf16(float lo, float hi) { uint32_t r; asm("cvt.rn.bf16x2.f32 %0, %1, %2;" : "=r"(r) : "f"(hi), "f"(lo)); return r; }
__device__ __forceinline__ float ex2(float x) { float r; asm("ex2.approx.ftz.f32 %0, %1;" : "=f"(r) : "f"(x)); return r; }
__device__ __forceinline__ float rcp_fast(float x) { float r; asm("rcp.approx.ftz.f32 %0, %1;" : "=f"(r) : "f"(x)); return r; }
__device__ __forceinline__ void stsm_x4(uint32_t addr, uint32_t r0, uint32_t r1, uint32_t r2, uint32_t r3) {
  asm volatile("stmatrix.sync.aligned.m8n8.x4.shared.b16 [%0], {%1, %2, %3, %4};" ::"r"(addr), "r"(r0), "r"(r1), "r"(r2), "r"(r3) : "memory");
}
__device__ __forceinline__ void stsm_x4_t(uint32_t addr, uint32_t r0, uint32_t r1, uint32_t r2, uint32_t r3) {
  asm volatile("stmatrix.sync.aligned.m8n8.x4.trans.shared.b16 [%0], {%1, %2, %3, %4};" ::"r"(addr), "r"(r0), "r"(r1), "r"(r2), "r"(r3) : "memory");
}

__device__ __forceinline__ void wgmma_n112_ta(float (&d)[56], uint64_t da, uint64_t db, int sc) {
  asm volatile("{\n.reg .pred p;\nsetp.ne.b32 p, %58, 0;\n"
    "wgmma.mma_async.sync.aligned.m64n112k16.f32.bf16.bf16 "
    "{%0, %1, %2, %3, %4, %5, %6, %7, %8, %9, %10, %11, %12, %13, %14, %15, %16, %17, %18, %19, %20, %21, %22, %23, %24, %25, %26, %27, %28, %29, %30, %31, %32, %33, %34, %35, %36, %37, %38, %39, %40, %41, %42, %43, %44, %45, %46, %47, %48, %49, %50, %51, %52, %53, %54, %55}, "
    "%56, %57, p, 1, 1, 1, 0;\n}\n"
    : "+f"(d[0]), "+f"(d[1]), "+f"(d[2]), "+f"(d[3]), "+f"(d[4]), "+f"(d[5]), "+f"(d[6]), "+f"(d[7]), "+f"(d[8]), "+f"(d[9]), "+f"(d[10]), "+f"(d[11]), "+f"(d[12]), "+f"(d[13]), "+f"(d[14]), "+f"(d[15]), "+f"(d[16]), "+f"(d[17]), "+f"(d[18]), "+f"(d[19]), "+f"(d[20]), "+f"(d[21]), "+f"(d[22]), "+f"(d[23]), "+f"(d[24]), "+f"(d[25]), "+f"(d[26]), "+f"(d[27]), "+f"(d[28]), "+f"(d[29]), "+f"(d[30]), "+f"(d[31]), "+f"(d[32]), "+f"(d[33]), "+f"(d[34]), "+f"(d[35]), "+f"(d[36]), "+f"(d[37]), "+f"(d[38]), "+f"(d[39]), "+f"(d[40]), "+f"(d[41]), "+f"(d[42]), "+f"(d[43]), "+f"(d[44]), "+f"(d[45]), "+f"(d[46]), "+f"(d[47]), "+f"(d[48]), "+f"(d[49]), "+f"(d[50]), "+f"(d[51]), "+f"(d[52]), "+f"(d[53]), "+f"(d[54]), "+f"(d[55])
    : "l"(da), "l"(db), "r"(sc));
}

__device__ __forceinline__ void wgmma_n64_ss(float (&d)[32], uint64_t da, uint64_t db, int sc) {
  asm volatile("{\n.reg .pred p;\nsetp.ne.b32 p, %34, 0;\n"
    "wgmma.mma_async.sync.aligned.m64n64k16.f32.bf16.bf16 "
    "{%0, %1, %2, %3, %4, %5, %6, %7, %8, %9, %10, %11, %12, %13, %14, %15, %16, %17, %18, %19, %20, %21, %22, %23, %24, %25, %26, %27, %28, %29, %30, %31}, "
    "%32, %33, p, 1, 1, 0, 0;\n}\n"
    : "+f"(d[0]), "+f"(d[1]), "+f"(d[2]), "+f"(d[3]), "+f"(d[4]), "+f"(d[5]), "+f"(d[6]), "+f"(d[7]), "+f"(d[8]), "+f"(d[9]), "+f"(d[10]), "+f"(d[11]), "+f"(d[12]), "+f"(d[13]), "+f"(d[14]), "+f"(d[15]), "+f"(d[16]), "+f"(d[17]), "+f"(d[18]), "+f"(d[19]), "+f"(d[20]), "+f"(d[21]), "+f"(d[22]), "+f"(d[23]), "+f"(d[24]), "+f"(d[25]), "+f"(d[26]), "+f"(d[27]), "+f"(d[28]), "+f"(d[29]), "+f"(d[30]), "+f"(d[31])
    : "l"(da), "l"(db), "r"(sc));
}

__device__ __forceinline__ void wgmma_n128_rs(float (&d)[64], uint32_t a0, uint32_t a1, uint32_t a2, uint32_t a3, uint64_t db, int sc) {
  asm volatile("{\n.reg .pred p;\nsetp.ne.b32 p, %69, 0;\n"
    "wgmma.mma_async.sync.aligned.m64n128k16.f32.bf16.bf16 "
    "{%0, %1, %2, %3, %4, %5, %6, %7, %8, %9, %10, %11, %12, %13, %14, %15, %16, %17, %18, %19, %20, %21, %22, %23, %24, %25, %26, %27, %28, %29, %30, %31, %32, %33, %34, %35, %36, %37, %38, %39, %40, %41, %42, %43, %44, %45, %46, %47, %48, %49, %50, %51, %52, %53, %54, %55, %56, %57, %58, %59, %60, %61, %62, %63}, "
    "{%64, %65, %66, %67}, %68, p, 1, 1, 1;\n}\n"
    : "+f"(d[0]), "+f"(d[1]), "+f"(d[2]), "+f"(d[3]), "+f"(d[4]), "+f"(d[5]), "+f"(d[6]), "+f"(d[7]), "+f"(d[8]), "+f"(d[9]), "+f"(d[10]), "+f"(d[11]), "+f"(d[12]), "+f"(d[13]), "+f"(d[14]), "+f"(d[15]), "+f"(d[16]), "+f"(d[17]), "+f"(d[18]), "+f"(d[19]), "+f"(d[20]), "+f"(d[21]), "+f"(d[22]), "+f"(d[23]), "+f"(d[24]), "+f"(d[25]), "+f"(d[26]), "+f"(d[27]), "+f"(d[28]), "+f"(d[29]), "+f"(d[30]), "+f"(d[31]), "+f"(d[32]), "+f"(d[33]), "+f"(d[34]), "+f"(d[35]), "+f"(d[36]), "+f"(d[37]), "+f"(d[38]), "+f"(d[39]), "+f"(d[40]), "+f"(d[41]), "+f"(d[42]), "+f"(d[43]), "+f"(d[44]), "+f"(d[45]), "+f"(d[46]), "+f"(d[47]), "+f"(d[48]), "+f"(d[49]), "+f"(d[50]), "+f"(d[51]), "+f"(d[52]), "+f"(d[53]), "+f"(d[54]), "+f"(d[55]), "+f"(d[56]), "+f"(d[57]), "+f"(d[58]), "+f"(d[59]), "+f"(d[60]), "+f"(d[61]), "+f"(d[62]), "+f"(d[63])
    : "r"(a0), "r"(a1), "r"(a2), "r"(a3), "l"(db), "r"(sc));
}

__device__ __forceinline__ void store_tile_t(uint32_t blk, const uint32_t (&pk)[28], int wi, int lane) {
  const int mi = lane >> 3, r = lane & 7;
  const uint32_t base = blk + (uint32_t)(((mi >> 1) * 8 + r) * 128 + (((2 * wi + (mi & 1)) ^ r) << 4));
#pragma unroll
  for (int i = 0; i < 7; i++) stsm_x4_t(base + i * 2048, pk[4 * i], pk[4 * i + 1], pk[4 * i + 2], pk[4 * i + 3]);
}
__device__ __forceinline__ void pack_tile(uint32_t (&pk)[28], const float (&a)[56]) {
#pragma unroll
  for (int i = 0; i < 28; i++) pk[i] = pack_bf16(a[2 * i], a[2 * i + 1]);
}

struct RowStat { float m0, m1, l0, l1; };

__device__ __forceinline__ void store_o_tile(uint32_t blk0, int row0, const float (&O)[64], RowStat& st) {
  int tid_;
  asm volatile("mov.u32 %0, %%tid.x;" : "=r"(tid_));
  const int lane = tid_ & 31, wi = (tid_ >> 5) & 3;
  float l0 = st.l0, l1 = st.l1;
  l0 += __shfl_xor_sync(0xffffffffu, l0, 1); l0 += __shfl_xor_sync(0xffffffffu, l0, 2);
  l1 += __shfl_xor_sync(0xffffffffu, l1, 1); l1 += __shfl_xor_sync(0xffffffffu, l1, 2);
  const float i0 = rcp_fast(l0), i1 = rcp_fast(l1);
  const int mi = lane >> 3, r = lane & 7;
  const int rowb = row0 + 16 * wi;
  if (rowb < SQ) {
    const uint32_t base = blk0 + (uint32_t)((rowb + (mi & 1) * 8 + r) * 128);
#pragma unroll
    for (int i = 0; i < 16; i += 2) {
      const int cg = (i & 7) + (mi >> 1);
      const uint32_t addr = base + (uint32_t)((i >> 3) * BLK) + (uint32_t)((cg ^ r) << 4);
      stsm_x4(addr, pack_bf16(O[4 * i] * i0, O[4 * i + 1] * i0), pack_bf16(O[4 * i + 2] * i1, O[4 * i + 3] * i1),
              pack_bf16(O[4 * i + 4] * i0, O[4 * i + 5] * i0), pack_bf16(O[4 * i + 6] * i1, O[4 * i + 7] * i1));
    }
  }
}

constexpr float SCALE_LOG2E = 0.08838834764831845f * 1.4426950408889634f;

__device__ __forceinline__ void softmax_max(const float (&S)[32], float& x0, float& x1) {
  x0 = fmaxf(S[0], S[1]); x1 = fmaxf(S[2], S[3]);
#pragma unroll
  for (int i = 1; i < 8; i++) {
    x0 = fmaxf(x0, fmaxf(S[4 * i], S[4 * i + 1]));
    x1 = fmaxf(x1, fmaxf(S[4 * i + 2], S[4 * i + 3]));
  }
  x0 = fmaxf(x0, __shfl_xor_sync(0xffffffffu, x0, 1)); x1 = fmaxf(x1, __shfl_xor_sync(0xffffffffu, x1, 1));
  x0 = fmaxf(x0, __shfl_xor_sync(0xffffffffu, x0, 2)); x1 = fmaxf(x1, __shfl_xor_sync(0xffffffffu, x1, 2));
}
__device__ __forceinline__ void softmax_rescale(float (&O)[64], RowStat& st, float& mc0, float& mc1) {
  const float n0 = fmaxf(st.m0, mc0), n1 = fmaxf(st.m1, mc1);
  const float a0 = ex2((st.m0 - n0) * SCALE_LOG2E), a1 = ex2((st.m1 - n1) * SCALE_LOG2E);
  st.m0 = n0; st.m1 = n1;
  mc0 = n0 * SCALE_LOG2E; mc1 = n1 * SCALE_LOG2E;
  st.l0 *= a0; st.l1 *= a1;
#pragma unroll
  for (int i = 0; i < 16; i++) { O[4 * i] *= a0; O[4 * i + 1] *= a0; O[4 * i + 2] *= a1; O[4 * i + 3] *= a1; }
}
__device__ __forceinline__ void softmax_exp(const float (&S)[32], uint32_t (&P)[16], RowStat& st, float mc0, float mc1) {
  float s0 = 0.f, s1 = 0.f;
#pragma unroll
  for (int i = 0; i < 8; i++) {
    const float p0 = ex2(fmaf(S[4 * i], SCALE_LOG2E, -mc0)), p1 = ex2(fmaf(S[4 * i + 1], SCALE_LOG2E, -mc0));
    const float p2 = ex2(fmaf(S[4 * i + 2], SCALE_LOG2E, -mc1)), p3 = ex2(fmaf(S[4 * i + 3], SCALE_LOG2E, -mc1));
    s0 += p0 + p1; s1 += p2 + p3;
    P[2 * i] = pack_bf16(p0, p1); P[2 * i + 1] = pack_bf16(p2, p3);
  }
  st.l0 += s0; st.l1 += s1;
}

__device__ __forceinline__ void issue_s(float (&S)[32], uint32_t qaddr, uint32_t kaddr) {
#pragma unroll
  for (int kk = 0; kk < 8; kk++)
    wgmma_n64_ss(S, mkdesc(qaddr + (kk >> 2) * BLK + (kk & 3) * 32, 1), mkdesc(kaddr + (kk >> 2) * 8192 + (kk & 3) * 32, 1), kk != 0);
}
__device__ __forceinline__ void issue_pv(float (&O)[64], const uint32_t (&P)[16], uint32_t vaddr) {
#pragma unroll
  for (int kk = 0; kk < 4; kk++)
    wgmma_n128_rs(O, P[4 * kk], P[4 * kk + 1], P[4 * kk + 2], P[4 * kk + 3], mkdesc(vaddr + kk * 2048, 8192 >> 4), 1);
}

__device__ __forceinline__ int o_tile_of_step(int j, int s) {
  if (s == 8) return j;
  if (j == 0) return s == 7 ? 8 : s + 1;
  return s == 0 ? 8 : ((j + s) & 7);
}

__device__ __forceinline__ void wait_flag(const uint32_t* f) {
  uint32_t v, it = 0;
  do {
    asm volatile("ld.acquire.gpu.global.u32 %0, [%1];" : "=r"(v) : "l"(f) : "memory");
    if (++it > SPIN_LIMIT) break;
  } while (v == 0);
}
__device__ __forceinline__ void add_partial(float (&a)[56], const uint4 (&v)[7]) {
#pragma unroll
  for (int i = 0; i < 7; i++) {
    const uint32_t w[4] = {v[i].x, v[i].y, v[i].z, v[i].w};
#pragma unroll
    for (int c = 0; c < 4; c++) {
      a[8 * i + 2 * c] += __uint_as_float(w[c] << 16);
      a[8 * i + 2 * c + 1] += __uint_as_float(w[c] & 0xffff0000u);
    }
  }
}
__device__ __forceinline__ void load_partial(uint4 (&v)[7], const uint4* p) {
#pragma unroll
  for (int i = 0; i < 7; i++) v[i] = __ldcg(p + i * 128);
}

__global__ void __cluster_dims__(2, 1, 1) __launch_bounds__(NTHREADS, 1)
gqa_fused_kernel(const __grid_constant__ CUtensorMap tm_x, const __grid_constant__ CUtensorMap tm_k,
                 const __grid_constant__ CUtensorMap tm_v, const __grid_constant__ CUtensorMap tm_wq,
                 const __grid_constant__ CUtensorMap tm_wo, const __grid_constant__ CUtensorMap tm_out) {
  extern __shared__ __align__(1024) uint8_t smem[];
  const uint32_t sb = smem_u32(smem);
  const uint32_t slots = sb + OFF_SLOTS;
  const uint32_t bar_full = sb + OFF_BARS, bar_empty = bar_full + NFILL * 8, bar_x = bar_empty + NFILL * 8;
  const int tid = threadIdx.x, lane = tid & 31;
  const int wg = __shfl_sync(0xffffffffu, tid >> 7, 0), wi = __shfl_sync(0xffffffffu, (tid >> 5) & 3, 0);
  const uint32_t rank = blockIdx.x & 1;
  const int cl = blockIdx.x >> 1;
  const int j = cl & 7, b = (cl >> 3) * 2 + (int)rank;

  TSTAMP(0);
  if (tid < NBARS) {
    uint32_t cnt = 1;
    if (tid >= NFILL && tid < 2 * NFILL) {
      const int n = tid - NFILL;
      cnt = (n >= FILL_O0 - NSLOT && n < FILL_O0) ? 16 : 8;
    }
    mbar_init(bar_full + tid * 8, cnt);
    asm volatile("fence.mbarrier_init.release.cluster;" ::: "memory");
  }
  if (tid == 256) { prefetch_tmap(&tm_x); prefetch_tmap(&tm_wq); prefetch_tmap(&tm_k); prefetch_tmap(&tm_v); prefetch_tmap(&tm_wo); prefetch_tmap(&tm_out); }
  __syncthreads();
  asm volatile("barrier.cluster.arrive.relaxed.aligned;" ::: "memory");
  if (tid == 256 + 64) {
#pragma unroll 1
    for (int k = 0; k < 9; k++) {
      mbar_expect_tx(bar_x + k * 8, BLK);
      tma_2d(sb + k * BLK, &tm_x, k * 64, b * SQ, bar_x + k * 8);
    }
  }
  __syncwarp();
  asm volatile("barrier.cluster.wait.acquire.aligned;" ::: "memory");

  if (wg == 2) {
    asm volatile("setmaxnreg.dec.sync.aligned.u32 24;");
    if (wi < 2 && lane == 0) {
#pragma unroll 1
      for (int n = wi; n < NFILL; n += 2) {
        const uint32_t dst = slots + (n % NSLOT) * SLOT_BYTES, fb = bar_full + n * 8;
        if (n >= NSLOT) mbar_wait_cluster(bar_empty + (n - NSLOT) * 8);
        mbar_expect_tx(fb, SLOT_BYTES);
        if (n < FILL_KV0) {
          const int u = n / 18, k = (n % 18) >> 1, w = n & 1;
          tma_2d_mc(dst + rank * 8192, &tm_wq, (4 * j + 2 * u + w) * DH + (int)rank * 64, k * 64, fb);
        } else if (n < FILL_O0) {
          const int jj = (n - FILL_KV0) >> 1;
          const int row = (b * HKV + 2 * j) * SK + jj * 64;
          tma_3d(dst, (n & 1) ? &tm_v : &tm_k, 0, row, 0, fb);
        } else {
          const int s = (n - FILL_O0) >> 2, kq = (n - FILL_O0) & 3;
          tma_2d_mc(dst + rank * 8192, &tm_wo, o_tile_of_step(j, s) * 64, j * 512 + kq * 128 + (int)rank * 64, fb);
        }
      }
    }
  } else {
    asm volatile("setmaxnreg.inc.sync.aligned.u32 240;");
    const uint32_t peer_empty = mapa(bar_empty, rank ^ 1);
    const uint32_t dsb = sb & 0x3FFFF, dslots = dsb + OFF_SLOTS;
    auto release_both = [&](int n) { if (lane == 0) { mbar_arrive(bar_empty + n * 8); mbar_arrive_remote(peer_empty + n * 8); } };
    auto release_kv = [&](int n) {
      if (lane == 0) { mbar_arrive(bar_empty + n * 8); if (n >= FILL_O0 - NSLOT) mbar_arrive_remote(peer_empty + n * 8); }
    };
    TSTAMP(1);
    {
      float acc0[56], acc1[56];
      uint32_t q0[28], q1[28];
#pragma unroll 1
      for (int u = 0; u < 2; u++) {
#pragma unroll 1
        for (int k = 0; k < 9; k++) {
          const int n = u * 18 + k * 2 + wg;
          const uint32_t sl = dslots + (n % NSLOT) * SLOT_BYTES, xs = dsb + k * BLK;
          if (u == 0) mbar_wait(bar_x + k * 8);
          mbar_wait(bar_full + n * 8);
          WG_FENCE();
#pragma unroll
          for (int kk = 0; kk < 4; kk++) {
            const uint64_t db = mkdesc(xs + kk * 32, 1);
            wgmma_n112_ta(acc0, mkdesc(sl + kk * 2048, 1), db, (k | kk) != 0);
            wgmma_n112_ta(acc1, mkdesc(sl + 8192 + kk * 2048, 1), db, (k | kk) != 0);
          }
          WG_COMMIT();
          if (k > 0) { WG_WAIT(1); release_both(n - 2); }
        }
        WG_WAIT(0);
        release_both(u * 18 + 16 + wg);
        pin(acc0); pin(acc1);
        if (u == 0) { pack_tile(q0, acc0); pack_tile(q1, acc1); }
      }
      TSTAMP(2);
      named_bar(1, 256);
      store_tile_t(sb + (2 * wg) * BLK, q0, wi, lane);
      store_tile_t(sb + (2 * wg + 1) * BLK, q1, wi, lane);
      pack_tile(q0, acc0); pack_tile(q1, acc1);
      store_tile_t(sb + (4 + 2 * wg) * BLK, q0, wi, lane);
      store_tile_t(sb + (4 + 2 * wg + 1) * BLK, q1, wi, lane);
      fence_async_smem();
      named_bar(2 + wg, 128);
    }
    TSTAMP(3);
    {
      float Oa[64], Ob[64], Sa[32], Sb[32];
      uint32_t P[16];
      RowStat sa, sbt;
#pragma unroll
      for (int i = 0; i < 64; i++) { Oa[i] = 0.f; Ob[i] = 0.f; }
#pragma unroll
      for (int i = 0; i < 16; i++) P[i] = 0u;
      sa.m0 = sa.m1 = sbt.m0 = sbt.m1 = -INFINITY; sa.l0 = sa.l1 = sbt.l0 = sbt.l1 = 0.f;
      const uint32_t qblk = sb + (2 * wg) * BLK, dq = dsb + (2 * wg) * BLK;
      int slot_k = FILL_KV0 % NSLOT;
      pin(Oa); pin(Ob);
      mbar_wait(bar_full + FILL_KV0 * 8);
      WG_FENCE();
      issue_s(Sa, dq, dslots + slot_k * SLOT_BYTES); WG_COMMIT();
      WG_WAIT(0);
      uint32_t vprev = dslots + slot_k * SLOT_BYTES;
#pragma unroll 1
      for (int jj = 0; jj < 16; jj++) {
        const int nk = FILL_KV0 + 2 * jj;
        const uint32_t kcur = dslots + slot_k * SLOT_BYTES, vaddr = kcur + SLOT_BYTES;
        slot_k = (slot_k == NSLOT - 2) ? 0 : slot_k + 2;
        const uint32_t knext = dslots + slot_k * SLOT_BYTES;
        float mc0, mc1;
        WG_FENCE();
        issue_pv(Ob, P, vprev);
        WG_COMMIT();
        issue_s(Sb, dq + (jj >= 8 ? 4 * BLK : 0) + 64 * 128, kcur);
        WG_COMMIT();
        pin(Sa); pin(Oa);
        softmax_max(Sa, mc0, mc1);
        WG_WAIT(1);
        pin(Sa);
        if (jj > 0) release_kv(nk - 1);
        if (jj == 8) {
          store_o_tile(qblk, 0, Oa, sa);
          sa.m0 = sa.m1 = -INFINITY; sa.l0 = sa.l1 = 0.f;
        }
        softmax_rescale(Oa, sa, mc0, mc1);
        softmax_exp(Sa, P, sa, mc0, mc1);
        mbar_wait(bar_full + (nk + 1) * 8);
        if (jj < 15) mbar_wait(bar_full + (nk + 2) * 8);
        WG_FENCE();
        issue_pv(Oa, P, vaddr); WG_COMMIT();
        issue_s(Sa, dq + (jj >= 7 ? 4 * BLK : 0), knext);
        WG_COMMIT();
        WG_WAIT(2);
        pin(Sb); pin(Ob);
        release_kv(nk);
        softmax_max(Sb, mc0, mc1);
        WG_WAIT(1);
        pin(Sb);
        if (jj == 8) {
          store_o_tile(qblk, 64, Ob, sbt);
          sbt.m0 = sbt.m1 = -INFINITY; sbt.l0 = sbt.l1 = 0.f;
        }
        softmax_rescale(Ob, sbt, mc0, mc1);
        softmax_exp(Sb, P, sbt, mc0, mc1);
        WG_WAIT(0);
        vprev = vaddr;
      }
      WG_FENCE();
      issue_pv(Ob, P, vprev); WG_COMMIT();
      pin(Oa);
      store_o_tile(qblk + 4 * BLK, 0, Oa, sa);
      WG_WAIT(0);
      pin(Ob);
      release_kv(FILL_O0 - 1);
      store_o_tile(qblk + 4 * BLK, 64, Ob, sbt);
      fence_async_smem();
      TSTAMP(4);
      named_bar(1, 256);
    }
    TSTAMP(5);
    {
      const int t128 = tid & 127;
#pragma unroll 1
      for (int s = wg; s < 9; s += 2) {
        const int tile = o_tile_of_step(j, s);
        const bool own = (s == 8) || (j == 0 && s == 7);
        const uint4* pbase = g_part + (size_t)((b * 9 + tile) * 8) * (7 * 128) + t128;
        uint32_t* fbase = g_flag + (b * 9 + tile) * 8;
        float acc[56];
#pragma unroll
        for (int i = 0; i < 56; i++) acc[i] = 0.f;
        if (own) {
#pragma unroll 1
          for (int d = 1; d <= 5; d++) {
            const int src = (j - d) & 7;
            uint4 v[7];
            wait_flag(fbase + src);
            load_partial(v, pbase + src * (7 * 128));
            add_partial(acc, v);
          }
        }
#pragma unroll 1
        for (int kq = 0; kq < 4; kq++) {
          const int n = FILL_O0 + s * 4 + kq;
          const uint32_t sl = dslots + (n % NSLOT) * SLOT_BYTES, ob = dsb + (2 * kq) * BLK;
          mbar_wait(bar_full + n * 8);
          WG_FENCE();
#pragma unroll
          for (int kk = 0; kk < 8; kk++)
            wgmma_n112_ta(acc, mkdesc(sl + kk * 2048, 1), mkdesc(ob + (kk >> 2) * BLK + (kk & 3) * 32, 1), 1);
          WG_COMMIT();
          if (kq > 0) { WG_WAIT(1); if (n - 1 < NFILL - NSLOT) release_both(n - 1); }
        }
        uint32_t pk[28];
        if (!own) {
          WG_WAIT(0);
          pin(acc);
          if (FILL_O0 + s * 4 + 3 < NFILL - NSLOT) release_both(FILL_O0 + s * 4 + 3);
          pack_tile(pk, acc);
          uint4* dst = g_part + (size_t)((b * 9 + tile) * 8 + j) * (7 * 128) + t128;
#pragma unroll
          for (int i = 0; i < 7; i++) __stcg(dst + i * 128, make_uint4(pk[4 * i], pk[4 * i + 1], pk[4 * i + 2], pk[4 * i + 3]));
          named_bar(2 + wg, 128);
          if (t128 == 0) {
            __threadfence();
            asm volatile("st.relaxed.gpu.global.u32 [%0], %1;" ::"l"(fbase + j), "r"(1u) : "memory");
          }
        } else {
          uint4 v0[7], v1[7];
          wait_flag(fbase + ((j - 6) & 7));
          load_partial(v0, pbase + ((j - 6) & 7) * (7 * 128));
          wait_flag(fbase + ((j - 7) & 7));
          load_partial(v1, pbase + ((j - 7) & 7) * (7 * 128));
          WG_WAIT(0);
          pin(acc);
          add_partial(acc, v0);
          add_partial(acc, v1);
          pack_tile(pk, acc);
          const uint32_t stg = slots + ((FILL_O0 + s * 4 + 3) % NSLOT) * SLOT_BYTES;
          named_bar(2 + wg, 128);
          store_tile_t(stg, pk, wi, lane);
          fence_async_smem();
          if (t128 < 8 && t128 != j) fbase[t128] = 0;
          named_bar(2 + wg, 128);
          if (t128 == 0) {
            tma_store_2d(&tm_out, stg, tile * 64, b * SQ);
            asm volatile("cp.async.bulk.commit_group;" ::: "memory");
            asm volatile("cp.async.bulk.wait_group.read 0;" ::: "memory");
          }
        }
      }
    }
    TSTAMP(6);
  }
}

typedef CUresult (*EncodeFn)(CUtensorMap*, CUtensorMapDataType, cuuint32_t, void*, const cuuint64_t*, const cuuint64_t*,
                             const cuuint32_t*, const cuuint32_t*, CUtensorMapInterleave, CUtensorMapSwizzle,
                             CUtensorMapL2promotion, CUtensorMapFloatOOBfill);

void make_map(EncodeFn enc, CUtensorMap* m, const void* ptr, int rank, const cuuint64_t* dims, const cuuint64_t* strides,
              const cuuint32_t* box) {
  cuuint32_t es[3] = {1, 1, 1};
  enc(m, CU_TENSOR_MAP_DATA_TYPE_BFLOAT16, rank, const_cast<void*>(ptr), dims, strides, box, es, CU_TENSOR_MAP_INTERLEAVE_NONE,
      CU_TENSOR_MAP_SWIZZLE_128B, CU_TENSOR_MAP_L2_PROMOTION_L2_256B, CU_TENSOR_MAP_FLOAT_OOB_FILL_NONE);
}

}

extern "C" void kernel_launch(void* const* d_in, const int* in_sizes, int n_in, void* d_out, int out_size) {
  (void)in_sizes; (void)n_in; (void)out_size;
  static EncodeFn enc = nullptr;
  if (!enc) {
    void* fn = nullptr;
    cudaDriverEntryPointQueryResult qr;
    cudaGetDriverEntryPoint("cuTensorMapEncodeTiled", &fn, cudaEnableDefault, &qr);
    enc = (EncodeFn)fn;
    cudaFuncSetAttribute(gqa_fused_kernel, cudaFuncAttributeMaxDynamicSharedMemorySize, SMEM_BYTES);
  }
  CUtensorMap tx, tk, tv, twq, two, tout;
  {
    cuuint64_t d[2] = {DM, B_ * SQ}, s[1] = {DM * 2}; cuuint32_t bx[2] = {64, SQ};
    make_map(enc, &tx, d_in[0], 2, d, s, bx);
    make_map(enc, &tout, d_out, 2, d, s, bx);
  }
  {
    cuuint64_t d[3] = {64, (cuuint64_t)B_ * HKV * SK, 2}, s[2] = {DH * 2, 128}; cuuint32_t bx[3] = {64, 64, 2};
    make_map(enc, &tk, d_in[1], 3, d, s, bx);
    make_map(enc, &tv, d_in[2], 3, d, s, bx);
  }
  {
    cuuint64_t d[2] = {HQ * DH, DM}, s[1] = {HQ * DH * 2}; cuuint32_t bx[2] = {64, 64};
    make_map(enc, &twq, d_in[3], 2, d, s, bx);
  }
  {
    cuuint64_t d[2] = {DM, HQ * DH}, s[1] = {DM * 2}; cuuint32_t bx[2] = {64, 64};
    make_map(enc, &two, d_in[4], 2, d, s, bx);
  }
  gqa_fused_kernel<<<128, NTHREADS, SMEM_BYTES>>>(tx, tk, tv, twq, two, tout);
}
```

```cpp
#include <cuda_runtime.h>
#include <cuda_bf16.h>
#include <cuda.h>
#include <stdint.h>

namespace {

constexpr int B_ = 16, SQ = 112, DM = 576, HQ = 32, HKV = 16, SK = 512, DH = 128;
constexpr int NSLOT = 6;
constexpr int SLOT_BYTES = 16384;
constexpr int BLK = 112 * 128;
constexpr int NFILL_Q = 36, NFILL_KV = 32, NFILL_O = 36;
constexpr int FILL_KV0 = NFILL_Q, FILL_O0 = NFILL_Q + NFILL_KV, NFILL = FILL_O0 + NFILL_O;
constexpr int OFF_SLOTS = 8 * BLK;
constexpr int OFF_STAGE = OFF_SLOTS + NSLOT * SLOT_BYTES;
constexpr int OFF_BARS = OFF_STAGE + BLK;
constexpr int NBARS = 2 * NFILL + 9 + 1;
constexpr int SMEM_BYTES = OFF_BARS + NBARS * 8 + 64;
constexpr int NTHREADS = 384;
#define PF_ON 1
#define PF_DIST 10
#define PF_LSU 0
#define WQPF 1
#define KV_EF 0
#define PF_END 4
#define PF_Q0 8
#define PF_QS 6
#define PF_CHUNK 16384
#define PF_WO_AT 31
constexpr uint32_t SPIN_LIMIT = 1u << 22;

__device__ uint4 g_part[B_ * 8 * 8 * 8 * 128];
__device__ uint4 g_part8[B_ * 8 * 8 * 4 * 32];
__device__ uint32_t g_epoch[B_];

#define GSTAMP(k, n) do {} while (0)
#define DSTAMP(k, n) do {} while (0)
#define TSTAMP(i) do {} while (0)

__device__ __forceinline__ uint32_t smem_u32(const void* p) { return (uint32_t)__cvta_generic_to_shared(p); }
__device__ __forceinline__ void mbar_init(uint32_t bar, uint32_t cnt) { asm volatile("mbarrier.init.shared::cta.b64 [%0], %1;" ::"r"(bar), "r"(cnt) : "memory"); }
__device__ __forceinline__ void mbar_expect_tx(uint32_t bar, uint32_t bytes) { asm volatile("mbarrier.arrive.expect_tx.shared::cta.b64 _, [%0], %1;" ::"r"(bar), "r"(bytes) : "memory"); }
__device__ __forceinline__ void mbar_arrive_pred(uint32_t bar, bool p) { asm volatile("{\n.reg .pred p;\nsetp.ne.b32 p, %1, 0;\n@p mbarrier.arrive.shared::cta.b64 _, [%0];\n}\n" ::"r"(bar), "r"((int)p) : "memory"); }
__device__ __forceinline__ void mbar_arrive_remote_pred(uint32_t rbar, bool p) { asm volatile("{\n.reg .pred p;\nsetp.ne.b32 p, %1, 0;\n@p mbarrier.arrive.shared::cluster.b64 _, [%0];\n}\n" ::"r"(rbar), "r"((int)p) : "memory"); }
__device__ __forceinline__ void mbar_wait_sleep(uint32_t bar) {
  uint32_t done, it = 0;
  do {
    asm volatile("{\n.reg .pred p;\nmbarrier.try_wait.parity.shared::cta.b64 p, [%1], 0, %2;\nselp.u32 %0, 1, 0, p;\n}\n" : "=r"(done) : "r"(bar), "r"(100000u) : "memory");
    if (++it > 4096) break;
  } while (!done);
}
__device__ __forceinline__ void mbar_wait(uint32_t bar) {
  uint32_t done, it = 0;
  do {
    asm volatile("{\n.reg .pred p;\nmbarrier.try_wait.parity.shared::cta.b64 p, [%1], 0;\nselp.u32 %0, 1, 0, p;\n}\n" : "=r"(done) : "r"(bar) : "memory");
    if (++it > SPIN_LIMIT) break;
  } while (!done);
}
__device__ __forceinline__ uint32_t mapa(uint32_t addr, uint32_t cta) { uint32_t r; asm volatile("mapa.shared::cluster.u32 %0, %1, %2;" : "=r"(r) : "r"(addr), "r"(cta)); return r; }
__device__ __forceinline__ void tma_2d(uint32_t dst, const CUtensorMap* m, int c0, int c1, uint32_t bar) {
  asm volatile("cp.async.bulk.tensor.2d.shared::cluster.global.mbarrier::complete_tx::bytes [%0], [%1, {%3, %4}], [%2];" ::"r"(dst), "l"(m), "r"(bar), "r"(c0), "r"(c1) : "memory");
}
__device__ __forceinline__ void tma_2d_mc(uint32_t dst, const CUtensorMap* m, int c0, int c1, uint32_t bar) {
  asm volatile("cp.async.bulk.tensor.2d.shared::cluster.global.mbarrier::complete_tx::bytes.multicast::cluster [%0], [%1, {%3, %4}], [%2], %5;" ::"r"(dst), "l"(m), "r"(bar), "r"(c0), "r"(c1), "h"((uint16_t)3) : "memory");
}
__device__ __forceinline__ void tma_3d(uint32_t dst, const CUtensorMap* m, int c0, int c1, int c2, uint32_t bar) {
  asm volatile("cp.async.bulk.tensor.3d.shared::cluster.global.mbarrier::complete_tx::bytes [%0], [%1, {%3, %4, %5}], [%2];" ::"r"(dst), "l"(m), "r"(bar), "r"(c0), "r"(c1), "r"(c2) : "memory");
}
__device__ __forceinline__ void tma_3d_hint(uint32_t dst, const CUtensorMap* m, int c0, int c1, int c2, uint32_t bar, uint64_t pol) {
  asm volatile("cp.async.bulk.tensor.3d.shared::cluster.global.mbarrier::complete_tx::bytes.L2::cache_hint [%0], [%1, {%3, %4, %5}], [%2], %6;" ::"r"(dst), "l"(m), "r"(bar), "r"(c0), "r"(c1), "r"(c2), "l"(pol) : "memory");
}
__device__ __forceinline__ uint4 ld_relaxed_b128(const uint4* p) {
  uint4 v;
  asm volatile("{\n.reg .b64 l, h;\n.reg .b128 t;\nld.relaxed.gpu.global.b128 t, [%4];\nmov.b128 {l, h}, t;\n"
               "mov.b64 {%0, %1}, l;\nmov.b64 {%2, %3}, h;\n}\n" : "=r"(v.x), "=r"(v.y), "=r"(v.z), "=r"(v.w) : "l"(p) : "memory");
  return v;
}
__device__ __forceinline__ void l2_prefetch(const void* p, uint32_t bytes) { asm volatile("cp.async.bulk.prefetch.L2.global [%0], %1;" ::"l"(p), "r"(bytes) : "memory"); }
__device__ __forceinline__ void prefetch_line(const void* p) { asm volatile("prefetch.global.L2 [%0];" ::"l"(p)); }
__device__ __forceinline__ void prefetch_tmap(const CUtensorMap* m) { asm volatile("prefetch.tensormap [%0];" ::"l"(m) : "memory"); }
__device__ __forceinline__ bool elect_one() { uint32_t p; asm volatile("{\n.reg .pred p;\nelect.sync _|p, 0xffffffff;\nselp.u32 %0, 1, 0, p;\n}\n" : "=r"(p)); return p != 0; }
__device__ __forceinline__ void named_bar(int id, int n) { asm volatile("bar.sync %0, %1;" ::"r"(id), "r"(n) : "memory"); }
__device__ __forceinline__ void named_arrive(int id, int n) { asm volatile("bar.arrive %0, %1;" ::"r"(id), "r"(n) : "memory"); }
__device__ __forceinline__ void fence_async_smem() { asm volatile("fence.proxy.async.shared::cta;" ::: "memory"); }
#define WG_FENCE() asm volatile("wgmma.fence.sync.aligned;" ::: "memory")
#define WG_COMMIT() asm volatile("wgmma.commit_group.sync.aligned;" ::: "memory")
#define WG_WAIT(n) asm volatile("wgmma.wait_group.sync.aligned %0;" ::"n"(n) : "memory")
template <int N> __device__ __forceinline__ void pin(float (&d)[N]) {
#pragma unroll
  for (int i = 0; i < N; i++) asm volatile("" : "+f"(d[i])::"memory");
}
__device__ __forceinline__ uint64_t mkdesc(uint32_t lo) { return ((uint64_t)(64u | (1u << 30)) << 32) | lo; }
__device__ __forceinline__ uint32_t pack_bf16(float lo, float hi) { uint32_t r; asm("cvt.rn.bf16x2.f32 %0, %1, %2;" : "=r"(r) : "f"(hi), "f"(lo)); return r; }
__device__ __forceinline__ float ex2(float x) { float r; asm("ex2.approx.ftz.f32 %0, %1;" : "=f"(r) : "f"(x)); return r; }
__device__ __forceinline__ float rcp_fast(float x) { float r; asm("rcp.approx.ftz.f32 %0, %1;" : "=f"(r) : "f"(x)); return r; }
__device__ __forceinline__ void stsm_x4(uint32_t addr, uint32_t r0, uint32_t r1, uint32_t r2, uint32_t r3) {
  asm volatile("stmatrix.sync.aligned.m8n8.x4.shared.b16 [%0], {%1, %2, %3, %4};" ::"r"(addr), "r"(r0), "r"(r1), "r"(r2), "r"(r3) : "memory");
}
__device__ __forceinline__ void stsm_x4_t(uint32_t addr, uint32_t r0, uint32_t r1, uint32_t r2, uint32_t r3) {
  asm volatile("stmatrix.sync.aligned.m8n8.x4.trans.shared.b16 [%0], {%1, %2, %3, %4};" ::"r"(addr), "r"(r0), "r"(r1), "r"(r2), "r"(r3) : "memory");
}

__device__ __forceinline__ void wgmma_n112_ta(float (&d)[56], uint64_t da, uint64_t db, int sc) {
  asm volatile("{\n.reg .pred p;\nsetp.ne.b32 p, %58, 0;\n"
    "wgmma.mma_async.sync.aligned.m64n112k16.f32.bf16.bf16 "
    "{%0, %1, %2, %3, %4, %5, %6, %7, %8, %9, %10, %11, %12, %13, %14, %15, %16, %17, %18, %19, %20, %21, %22, %23, %24, %25, %26, %27, %28, %29, %30, %31, %32, %33, %34, %35, %36, %37, %38, %39, %40, %41, %42, %43, %44, %45, %46, %47, %48, %49, %50, %51, %52, %53, %54, %55}, "
    "%56, %57, p, 1, 1, 1, 0;\n}\n"
    : "+f"(d[0]), "+f"(d[1]), "+f"(d[2]), "+f"(d[3]), "+f"(d[4]), "+f"(d[5]), "+f"(d[6]), "+f"(d[7]), "+f"(d[8]), "+f"(d[9]), "+f"(d[10]), "+f"(d[11]), "+f"(d[12]), "+f"(d[13]), "+f"(d[14]), "+f"(d[15]), "+f"(d[16]), "+f"(d[17]), "+f"(d[18]), "+f"(d[19]), "+f"(d[20]), "+f"(d[21]), "+f"(d[22]), "+f"(d[23]), "+f"(d[24]), "+f"(d[25]), "+f"(d[26]), "+f"(d[27]), "+f"(d[28]), "+f"(d[29]), "+f"(d[30]), "+f"(d[31]), "+f"(d[32]), "+f"(d[33]), "+f"(d[34]), "+f"(d[35]), "+f"(d[36]), "+f"(d[37]), "+f"(d[38]), "+f"(d[39]), "+f"(d[40]), "+f"(d[41]), "+f"(d[42]), "+f"(d[43]), "+f"(d[44]), "+f"(d[45]), "+f"(d[46]), "+f"(d[47]), "+f"(d[48]), "+f"(d[49]), "+f"(d[50]), "+f"(d[51]), "+f"(d[52]), "+f"(d[53]), "+f"(d[54]), "+f"(d[55])
    : "l"(da), "l"(db), "r"(sc));
}

__device__ __forceinline__ void wgmma_n64_ss(float (&d)[32], uint64_t da, uint64_t db, int sc) {
  asm volatile("{\n.reg .pred p;\nsetp.ne.b32 p, %34, 0;\n"
    "wgmma.mma_async.sync.aligned.m64n64k16.f32.bf16.bf16 "
    "{%0, %1, %2, %3, %4, %5, %6, %7, %8, %9, %10, %11, %12, %13, %14, %15, %16, %17, %18, %19, %20, %21, %22, %23, %24, %25, %26, %27, %28, %29, %30, %31}, "
    "%32, %33, p, 1, 1, 0, 0;\n}\n"
    : "+f"(d[0]), "+f"(d[1]), "+f"(d[2]), "+f"(d[3]), "+f"(d[4]), "+f"(d[5]), "+f"(d[6]), "+f"(d[7]), "+f"(d[8]), "+f"(d[9]), "+f"(d[10]), "+f"(d[11]), "+f"(d[12]), "+f"(d[13]), "+f"(d[14]), "+f"(d[15]), "+f"(d[16]), "+f"(d[17]), "+f"(d[18]), "+f"(d[19]), "+f"(d[20]), "+f"(d[21]), "+f"(d[22]), "+f"(d[23]), "+f"(d[24]), "+f"(d[25]), "+f"(d[26]), "+f"(d[27]), "+f"(d[28]), "+f"(d[29]), "+f"(d[30]), "+f"(d[31])
    : "l"(da), "l"(db), "r"(sc));
}

__device__ __forceinline__ void wgmma_n128_rs(float (&d)[64], uint32_t a0, uint32_t a1, uint32_t a2, uint32_t a3, uint64_t db, int sc) {
  asm volatile("{\n.reg .pred p;\nsetp.ne.b32 p, %69, 0;\n"
    "wgmma.mma_async.sync.aligned.m64n128k16.f32.bf16.bf16 "
    "{%0, %1, %2, %3, %4, %5, %6, %7, %8, %9, %10, %11, %12, %13, %14, %15, %16, %17, %18, %19, %20, %21, %22, %23, %24, %25, %26, %27, %28, %29, %30, %31, %32, %33, %34, %35, %36, %37, %38, %39, %40, %41, %42, %43, %44, %45, %46, %47, %48, %49, %50, %51, %52, %53, %54, %55, %56, %57, %58, %59, %60, %61, %62, %63}, "
    "{%64, %65, %66, %67}, %68, p, 1, 1, 1;\n}\n"
    : "+f"(d[0]), "+f"(d[1]), "+f"(d[2]), "+f"(d[3]), "+f"(d[4]), "+f"(d[5]), "+f"(d[6]), "+f"(d[7]), "+f"(d[8]), "+f"(d[9]), "+f"(d[10]), "+f"(d[11]), "+f"(d[12]), "+f"(d[13]), "+f"(d[14]), "+f"(d[15]), "+f"(d[16]), "+f"(d[17]), "+f"(d[18]), "+f"(d[19]), "+f"(d[20]), "+f"(d[21]), "+f"(d[22]), "+f"(d[23]), "+f"(d[24]), "+f"(d[25]), "+f"(d[26]), "+f"(d[27]), "+f"(d[28]), "+f"(d[29]), "+f"(d[30]), "+f"(d[31]), "+f"(d[32]), "+f"(d[33]), "+f"(d[34]), "+f"(d[35]), "+f"(d[36]), "+f"(d[37]), "+f"(d[38]), "+f"(d[39]), "+f"(d[40]), "+f"(d[41]), "+f"(d[42]), "+f"(d[43]), "+f"(d[44]), "+f"(d[45]), "+f"(d[46]), "+f"(d[47]), "+f"(d[48]), "+f"(d[49]), "+f"(d[50]), "+f"(d[51]), "+f"(d[52]), "+f"(d[53]), "+f"(d[54]), "+f"(d[55]), "+f"(d[56]), "+f"(d[57]), "+f"(d[58]), "+f"(d[59]), "+f"(d[60]), "+f"(d[61]), "+f"(d[62]), "+f"(d[63])
    : "r"(a0), "r"(a1), "r"(a2), "r"(a3), "l"(db), "r"(sc));
}

__device__ __forceinline__ void store_tile_t(uint32_t blk, const uint32_t (&pk)[28], int wi, int lane) {
  const int mi = lane >> 3, r = lane & 7;
  const uint32_t base = blk + (uint32_t)(((mi >> 1) * 8 + r) * 128 + (((2 * wi + (mi & 1)) ^ r) << 4));
#pragma unroll
  for (int i = 0; i < 7; i++) stsm_x4_t(base + i * 2048, pk[4 * i], pk[4 * i + 1], pk[4 * i + 2], pk[4 * i + 3]);
}
__device__ __forceinline__ void pack_tile(uint32_t (&pk)[28], const float (&a)[56]) {
#pragma unroll
  for (int i = 0; i < 28; i++) pk[i] = pack_bf16(a[2 * i], a[2 * i + 1]);
}

struct RowStat { float m0, m1, l0, l1; };

__device__ __forceinline__ void store_o_tile(uint32_t blk0, int row0, const float (&O)[64], RowStat& st) {
  int tid_;
  asm volatile("mov.u32 %0, %%tid.x;" : "=r"(tid_));
  const int lane = tid_ & 31, wi = (tid_ >> 5) & 3;
  float l0 = st.l0, l1 = st.l1;
  l0 += __shfl_xor_sync(0xffffffffu, l0, 1); l0 += __shfl_xor_sync(0xffffffffu, l0, 2);
  l1 += __shfl_xor_sync(0xffffffffu, l1, 1); l1 += __shfl_xor_sync(0xffffffffu, l1, 2);
  const float i0 = rcp_fast(l0), i1 = rcp_fast(l1);
  const int mi = lane >> 3, r = lane & 7;
  const int rowb = row0 + 16 * wi;
  if (rowb < SQ) {
    const uint32_t base = blk0 + (uint32_t)((rowb + (mi & 1) * 8 + r) * 128);
#pragma unroll
    for (int i = 0; i < 16; i += 2) {
      const int cg = (i & 7) + (mi >> 1);
      const uint32_t addr = base + (uint32_t)((i >> 3) * BLK) + (uint32_t)((cg ^ r) << 4);
      stsm_x4(addr, pack_bf16(O[4 * i] * i0, O[4 * i + 1] * i0), pack_bf16(O[4 * i + 2] * i1, O[4 * i + 3] * i1),
              pack_bf16(O[4 * i + 4] * i0, O[4 * i + 5] * i0), pack_bf16(O[4 * i + 6] * i1, O[4 * i + 7] * i1));
    }
  }
}

constexpr float SCALE_LOG2E = 0.08838834764831845f * 1.4426950408889634f;

constexpr float SUM_LIMIT = 4096.0f, SUM_LIMIT_LOG2 = 12.0f;
__device__ __forceinline__ void scale_sub(float (&S)[32], float m0, float m1) {
#pragma unroll
  for (int i = 0; i < 8; i++) {
    S[4 * i] = fmaf(S[4 * i], SCALE_LOG2E, -m0); S[4 * i + 1] = fmaf(S[4 * i + 1], SCALE_LOG2E, -m0);
    S[4 * i + 2] = fmaf(S[4 * i + 2], SCALE_LOG2E, -m1); S[4 * i + 3] = fmaf(S[4 * i + 3], SCALE_LOG2E, -m1);
  }
}
__device__ __forceinline__ void update_ref(float (&T)[32], float (&O)[64], RowStat& st, bool first) {
  float a0 = fmaxf(T[0], T[1]), a1 = fmaxf(T[2], T[3]), b0 = fmaxf(T[4], T[5]), b1 = fmaxf(T[6], T[7]);
#pragma unroll
  for (int i = 2; i < 8; i += 2) {
    a0 = fmaxf(a0, fmaxf(T[4 * i], T[4 * i + 1])); a1 = fmaxf(a1, fmaxf(T[4 * i + 2], T[4 * i + 3]));
    b0 = fmaxf(b0, fmaxf(T[4 * i + 4], T[4 * i + 5])); b1 = fmaxf(b1, fmaxf(T[4 * i + 6], T[4 * i + 7]));
  }
  float d0 = fmaxf(a0, b0), d1 = fmaxf(a1, b1);
  d0 = fmaxf(d0, __shfl_xor_sync(0xffffffffu, d0, 1)); d1 = fmaxf(d1, __shfl_xor_sync(0xffffffffu, d1, 1));
  d0 = fmaxf(d0, __shfl_xor_sync(0xffffffffu, d0, 2)); d1 = fmaxf(d1, __shfl_xor_sync(0xffffffffu, d1, 2));
  if (first) {
    st.m0 = d0; st.m1 = d1; st.l0 = 0.f; st.l1 = 0.f;
  } else {
    d0 = fmaxf(d0, 0.f); d1 = fmaxf(d1, 0.f);
    const float r0 = ex2(-d0), r1 = ex2(-d1);
    st.m0 += d0; st.m1 += d1; st.l0 *= r0; st.l1 *= r1;
#pragma unroll
    for (int i = 0; i < 16; i++) { O[4 * i] *= r0; O[4 * i + 1] *= r0; O[4 * i + 2] *= r1; O[4 * i + 3] *= r1; }
  }
#pragma unroll
  for (int i = 0; i < 8; i++) { T[4 * i] -= d0; T[4 * i + 1] -= d0; T[4 * i + 2] -= d1; T[4 * i + 3] -= d1; }
}
__device__ __forceinline__ bool softmax_exp(const float (&T)[32], uint32_t (&P)[16], float& l0, float& l1) {
  const bool ok_last = fmaxf(fmaxf(T[28], T[29]), fmaxf(T[30], T[31])) <= SUM_LIMIT_LOG2;
  bool bad = false;
#pragma unroll
  for (int i = 0; i < 8; i++) {
    if (i == 7) bad = __any_sync(0xffffffffu, !(fmaxf(l0, l1) <= SUM_LIMIT && ok_last));
    const float p0 = ex2(T[4 * i]), p1 = ex2(T[4 * i + 1]), p2 = ex2(T[4 * i + 2]), p3 = ex2(T[4 * i + 3]);
    if (i == 0) { l0 = p0; l1 = p2; } else { l0 += p0; l1 += p2; }
    l0 += p1; l1 += p3;
    P[2 * i] = pack_bf16(p0, p1); P[2 * i + 1] = pack_bf16(p2, p3);
  }
  return bad;
}
__device__ __forceinline__ void softmax_tile(float (&T)[32], float (&O)[64], uint32_t (&P)[16], RowStat& st) {
  float l0, l1;
  if (__builtin_expect(softmax_exp(T, P, l0, l1), 0)) {
    update_ref(T, O, st, false);
    softmax_exp(T, P, l0, l1);
  }
  st.l0 += l0; st.l1 += l1;
}

__device__ __forceinline__ void issue_s(float (&S)[32], uint32_t q16, uint32_t k16) {
  const uint64_t dq = mkdesc(q16), dk = mkdesc(k16);
#pragma unroll
  for (int kk = 0; kk < 8; kk++)
    wgmma_n64_ss(S, dq + ((kk >> 2) * (BLK / 16) + (kk & 3) * 2), dk + ((kk >> 2) * 512 + (kk & 3) * 2), kk != 0);
}
__device__ __forceinline__ void issue_pv(float (&O)[64], const uint32_t (&P)[16], uint32_t v16, int acc) {
  const uint64_t dv = mkdesc(v16 + (512u << 16));
#pragma unroll
  for (int kk = 0; kk < 4; kk++)
    wgmma_n128_rs(O, P[4 * kk], P[4 * kk + 1], P[4 * kk + 2], P[4 * kk + 3], dv + kk * 128, kk ? 1 : acc);
}

__device__ __forceinline__ int o_tile_of_step(int j, int s) { return s == 7 ? 8 : ((j + 1 + s - (s == 8)) & 7); }
__device__ __forceinline__ int o_quarter(int kq) { return ((kq & 1) << 1) | (kq >> 1); }

__device__ __forceinline__ void store_chunk(uint4* p, const float* a, float tagf) {
  asm volatile("st.relaxed.gpu.global.v4.b32 [%0], {%1, %2, %3, %4};" ::"l"(p), "r"(pack_bf16(a[0], a[1])),
               "r"(pack_bf16(a[2], a[3])), "r"(pack_bf16(a[4], a[5])), "r"(pack_bf16(a[6], tagf)) : "memory");
}
__device__ __forceinline__ void add_chunk(float* a, const uint4& v) {
  a[0] += __uint_as_float(v.x << 16); a[1] += __uint_as_float(v.x & 0xffff0000u);
  a[2] += __uint_as_float(v.y << 16); a[3] += __uint_as_float(v.y & 0xffff0000u);
  a[4] += __uint_as_float(v.z << 16); a[5] += __uint_as_float(v.z & 0xffff0000u);
  a[6] += __uint_as_float(v.w << 16);
}
__device__ __forceinline__ void load_chunks(uint4 (&v)[8], const uint4* p, int stride) {
#pragma unroll
  for (int i = 0; i < 8; i++) v[i] = ld_relaxed_b128(p + i * stride);
}
__device__ __forceinline__ void check_chunks(uint4 (&v)[8], const uint4* p, int stride, uint32_t tagbits) {
  uint32_t it = 0;
  for (;;) {
    uint32_t bad = 0;
#pragma unroll
    for (int i = 0; i < 8; i++) bad |= v[i].w ^ tagbits;
    if (!__any_sync(0xffffffffu, bad > 0xffffu) || ++it > SPIN_LIMIT) break;
    load_chunks(v, p, stride);
  }
}
__device__ __forceinline__ void add_partial(float (&a)[56], uint4 (&v)[8], const uint4* p, uint32_t tagbits) {
  check_chunks(v, p, 128, tagbits);
#pragma unroll
  for (int i = 0; i < 8; i++) add_chunk(a + 7 * i, v[i]);
}

__host__ __device__ constexpr uint32_t bar_count(int i) {
  return i >= 2 * NFILL ? 1
       : i >= NFILL ? ((i - NFILL >= FILL_O0 - NSLOT && i - NFILL < FILL_O0) ? 16 : 8)
       : (i > FILL_KV0 && i < FILL_O0 - 1) ? 2 : 1;
}
template <int W> __device__ __forceinline__ void init_barriers(uint32_t base, int w) {
  constexpr int NW = NTHREADS / 32, PER = (NBARS + NW - 1) / NW;
  if (w == W) {
#pragma unroll
    for (int i = W * PER; i < (W + 1) * PER && i < NBARS; i++) mbar_init(base + i * 8, bar_count(i));
  } else if constexpr (W + 1 < NW) {
    init_barriers<W + 1>(base, w);
  }
}

__global__ void __cluster_dims__(2, 1, 1) __launch_bounds__(NTHREADS, 1)
gqa_fused_kernel(const __grid_constant__ CUtensorMap tm_x, const __grid_constant__ CUtensorMap tm_k,
                 const __grid_constant__ CUtensorMap tm_v, const __grid_constant__ CUtensorMap tm_wq,
                 const __grid_constant__ CUtensorMap tm_wo, const uint8_t* __restrict__ gx,
                 const uint8_t* __restrict__ gk, const uint8_t* __restrict__ gv, const uint8_t* __restrict__ gwq,
                 const uint8_t* __restrict__ gwo, __nv_bfloat16* __restrict__ gout) {
  extern __shared__ __align__(1024) uint8_t smem[];
  const uint32_t sb = smem_u32(smem);
  const uint32_t slots = sb + OFF_SLOTS;
  const uint32_t bar_full = sb + OFF_BARS, bar_empty = bar_full + NFILL * 8, bar_x = bar_empty + NFILL * 8, bar_tag = bar_x + 9 * 8,
                 s_tag = bar_tag + 8, stage = sb + OFF_STAGE;
  const int tid = threadIdx.x, lane = tid & 31;
  const int wg = __shfl_sync(0xffffffffu, tid >> 7, 0), wi = __shfl_sync(0xffffffffu, (tid >> 5) & 3, 0);
  const uint32_t rank = blockIdx.x & 1;
  const int cl = blockIdx.x >> 1;
  const int j = cl & 7, b = (cl >> 3) * 2 + (int)rank;

  TSTAMP(0);
  if (tid == 256) { prefetch_tmap(&tm_x); prefetch_tmap(&tm_wq); }
  if (tid == 288) { prefetch_tmap(&tm_k); prefetch_tmap(&tm_v); prefetch_tmap(&tm_wo); }
  if (lane == 0) {
    init_barriers<0>(bar_full, wg * 4 + wi);
    asm volatile("fence.mbarrier_init.release.cluster;" ::: "memory");
  }
  __syncwarp();
  __syncthreads();
  asm volatile("barrier.cluster.arrive.relaxed.aligned;" ::: "memory");
  if (tid == 256) {
    mbar_expect_tx(bar_x, BLK);
    tma_2d(sb, &tm_x, 0, b * SQ, bar_x);
  }
  if (wg == 2 && wi == 3) {
    l2_prefetch(gwq + (size_t)(b + 16 * lane) * (HQ * DH * 2) + j * 1024, 1024);
    if (lane < 4) l2_prefetch(gwq + (size_t)(b + 16 * (32 + lane)) * (HQ * DH * 2) + j * 1024, 1024);
  }
  __syncwarp();
  asm volatile("barrier.cluster.wait.acquire.aligned;" ::: "memory");

  if (wg == 2) {
    asm volatile("setmaxnreg.dec.sync.aligned.u32 24;");
    if (wi < 2) {
      const uint32_t slot0 = slots + wi * SLOT_BYTES;
      uint32_t dst = slot0, fb = bar_full + wi * 8;
      auto next = [&]() { dst = (dst == slot0 + 4 * SLOT_BYTES) ? slot0 : dst + 2 * SLOT_BYTES; fb += 16; };
      constexpr uint32_t EMPTY_OFF = NFILL * 8 - NSLOT * 8;
      int c0 = (4 * j + wi) * DH + (int)rank * 64;
#pragma unroll 1
      for (int t = 0; t < 18; t++) {
        const int k = t < 9 ? t : t - 9;
        if (t == 9) c0 += 2 * DH;
        if (t >= 3) mbar_wait_sleep(fb + EMPTY_OFF);
        if (elect_one()) {
          DSTAMP(0, 2 * t + wi);
          mbar_expect_tx(fb, SLOT_BYTES);
          tma_2d_mc(dst + rank * 8192, &tm_wq, c0, k * 64, fb);
          if (t < 8 && wi == 1) {
            mbar_expect_tx(bar_x + (t + 1) * 8, BLK);
            tma_2d(t < 7 ? sb + (t + 1) * BLK : stage, &tm_x, (t + 1) * 64, b * SQ, bar_x + (t + 1) * 8);
          }
        }
        next();
      }
      const CUtensorMap* tm_kv = wi ? &tm_v : &tm_k;
      uint64_t pol;
      asm volatile("createpolicy.fractional.L2::evict_first.b64 %0, 1.0;" : "=l"(pol));
      int row = (b * HKV + 2 * j) * SK;
#pragma unroll 1
      for (int t = 0; t < 16; t++) {
        mbar_wait_sleep(fb + EMPTY_OFF + ((wi && t >= 3) ? 8 : 0));
        const uint32_t f = fb - ((!wi && t > 0) ? 8 : 0);
        if (elect_one()) {
          mbar_expect_tx(f, SLOT_BYTES);
          tma_3d(dst, tm_kv, 0, row, 0, f);
        }
        row += 64;
        next();
      }
      const int r0 = j * 512 + wi * 256 + (int)rank * 64;
#pragma unroll 1
      for (int t = 0; t < 18; t++) {
        mbar_wait_sleep(fb + EMPTY_OFF + ((wi && t < 2) ? 8 : 0));
        const int cw = o_tile_of_step(j, t >> 1) * 64;
        if (elect_one()) {
          DSTAMP(0, FILL_O0 + 2 * t + wi);
          mbar_expect_tx(fb, SLOT_BYTES);
          tma_2d_mc(dst + rank * 8192, &tm_wo, cw, r0 + (t & 1) * 128, fb);
        }
        next();
      }
    } else if (wi == 2) {
      const size_t kv0 = (size_t)(b * HKV + 2 * j) * SK * DH * 2;
#pragma unroll 1
      for (int c = 0; c < (PF_ON ? 32 : 0); c++) {
        mbar_wait_sleep(bar_full + (c < PF_DIST ? PF_Q0 + (c * PF_QS) / 2 : FILL_KV0 + (((c - PF_DIST) * (31 - PF_END) / (31 - PF_DIST)) | 1)) * 8);
        const uint8_t* p = ((c & 1) ? gv : gk) + kv0 + (size_t)(c >> 1) * 16384;
        if (lane < 16384 / PF_CHUNK) l2_prefetch(p + lane * PF_CHUNK, PF_CHUNK);
        if (c == PF_WO_AT && lane < 18) l2_prefetch(gwo + (size_t)j * (512 * DM * 2) + (size_t)b * 36864 + lane * 2048, 2048);
      }
    } else if (wi == 3) {
      if (lane == 0) {
        const uint32_t e = *reinterpret_cast<volatile uint32_t*>(g_epoch + b);
        asm volatile("st.shared.u32 [%0], %1;" ::"r"(s_tag), "r"((0x0800u + e % 0x7000u) << 16) : "memory");
        mbar_arrive_pred(bar_tag, true);
      }
    }
  } else {
    asm volatile("setmaxnreg.inc.sync.aligned.u32 240;");
    const uint32_t peer_empty = mapa(bar_empty, rank ^ 1);
    const uint32_t dsb = (sb & 0x3FFFF) >> 4, dslots = dsb + OFF_SLOTS / 16;
    constexpr uint32_t BLK16 = BLK / 16, SLOT16 = SLOT_BYTES / 16;
    auto release_both = [&](int n) { mbar_arrive_pred(bar_empty + n * 8, lane == 0); mbar_arrive_remote_pred(peer_empty + n * 8, lane == 0); };
    auto release_kv = [&](int n) {
      mbar_arrive_pred(bar_empty + n * 8, lane == 0);
      mbar_arrive_remote_pred(peer_empty + n * 8, lane == 0 && n >= FILL_O0 - NSLOT);
    };
    TSTAMP(1);
    const uint32_t qblk = sb + (2 * wg) * BLK, dq = dsb + (2 * wg) * BLK16;
    float Sa[32];
    {
      float acc0[56], acc1[56];
      uint32_t q0[28], q1[28];
      auto q_step = [&](int n, int k) {
        const uint64_t da = mkdesc(dslots + (n % NSLOT) * SLOT16), db = mkdesc(dsb + (k < 8 ? k * BLK16 : OFF_STAGE / 16));
        mbar_wait(bar_full + n * 8);
        if ((tid & 127) == 0) DSTAMP(2, n);
        WG_FENCE();
#pragma unroll
        for (int kk = 0; kk < 4; kk++) {
          wgmma_n112_ta(acc0, da + kk * 128, db + kk * 2, (k | kk) != 0);
          wgmma_n112_ta(acc1, da + (512 + kk * 128), db + kk * 2, (k | kk) != 0);
        }
        WG_COMMIT();
        if (k > 0) { WG_WAIT(1); release_both(n - 2); }
      };
#pragma unroll 1
      for (int k = 0; k < 9; k++) {
        mbar_wait(bar_x + k * 8);
        q_step(k * 2 + wg, k);
      }
      WG_WAIT(0);
      release_both(16 + wg);
      pin(acc0); pin(acc1);
      pack_tile(q0, acc0); pack_tile(q1, acc1);
#pragma unroll 1
      for (int k = 0; k < 9; k++) {
        q_step(18 + k * 2 + wg, k);
        if (k == 4 - 2 * wg) named_arrive(4 + (wg ^ 1), 256);
        if (k == 8 - 2 * wg) named_arrive(6 + (wg ^ 1), 256);
        if (k == 3 + 3 * wg) {
          named_bar(4 + wg, 256);
          store_tile_t(qblk, q0, wi, lane);
          store_tile_t(qblk + BLK, q1, wi, lane);
          fence_async_smem();
        }
        if (k == 7) named_bar(2 + wg, 128);
      }
      TSTAMP(2);
      mbar_wait(bar_full + FILL_KV0 * 8);
      WG_FENCE();
      issue_s(Sa, dq, dslots + (FILL_KV0 % NSLOT) * SLOT16);
      WG_COMMIT();
      WG_WAIT(1);
      release_both(34 + wg);
      pin(acc0); pin(acc1);
      pack_tile(q0, acc0); pack_tile(q1, acc1);
      named_bar(6 + wg, 256);
      store_tile_t(qblk + 4 * BLK, q0, wi, lane);
      store_tile_t(qblk + 5 * BLK, q1, wi, lane);
      fence_async_smem();
    }
    TSTAMP(3);
    {
      float Oa[64], Ob[64], Sb[32];
      uint32_t P[16];
      RowStat sa, sbt;
      WG_WAIT(0);
#pragma unroll
      for (int i = 0; i < 64; i++) { Oa[i] = 0.f; Ob[i] = 0.f; }
#pragma unroll
      for (int i = 0; i < 16; i++) P[i] = 0u;
      sa.m0 = sa.m1 = sbt.m0 = sbt.m1 = 0.f; sa.l0 = sa.l1 = sbt.l0 = sbt.l1 = 0.f;
      int slot_k = FILL_KV0 % NSLOT;
      pin(Oa); pin(Ob);
      if (wg == 1) named_arrive(4, 256);
      uint32_t vprev = dslots + slot_k * SLOT16;
#pragma unroll 1
      for (int jj = 0; jj < 16; jj++) {
        const int nk = FILL_KV0 + 2 * jj;
        const uint32_t kcur = dslots + slot_k * SLOT16, vaddr = kcur + SLOT16;
        slot_k = (slot_k == NSLOT - 2) ? 0 : slot_k + 2;
        const uint32_t knext = dslots + slot_k * SLOT16;
        const bool first = (jj & 7) == 0;
        named_bar(4 + wg, 256);
        WG_FENCE();
        issue_pv(Ob, P, vprev, (jj & 7) != 1);
        WG_COMMIT();
        pin(Sa);
        scale_sub(Sa, first ? 0.f : sa.m0, first ? 0.f : sa.m1);
        pin(Sa);
        issue_s(Sb, dq + (jj >= 8 ? 4 * BLK16 : 0) + 512, kcur);
        WG_COMMIT();
        named_arrive(4 + (wg ^ 1), 256);
        mbar_wait(bar_full + (nk + 1) * 8);
        WG_WAIT(1);
        pin(Oa); pin(Sa);
        if (__builtin_expect(first, 0)) {
          if (jj == 8) store_o_tile(qblk, 0, Oa, sa);
          update_ref(Sa, Oa, sa, true);
        }
        softmax_tile(Sa, Oa, P, sa);
        WG_WAIT(0);
        release_kv(nk);
        named_bar(4 + wg, 256);
        WG_FENCE();
        issue_pv(Oa, P, vaddr, !first);
        WG_COMMIT();
        pin(Sb);
        scale_sub(Sb, first ? 0.f : sbt.m0, first ? 0.f : sbt.m1);
        pin(Sb);
        issue_s(Sa, dq + (jj >= 7 ? 4 * BLK16 : 0), knext);
        WG_COMMIT();
        named_arrive(4 + (wg ^ 1), 256);
        WG_WAIT(1);
        pin(Ob); pin(Sb);
        if (__builtin_expect(first, 0)) {
          if (jj == 8) store_o_tile(qblk, 64, Ob, sbt);
          update_ref(Sb, Ob, sbt, true);
        }
        softmax_tile(Sb, Ob, P, sbt);
        WG_WAIT(0);
        vprev = vaddr;
      }
      if (wg == 0) named_bar(4, 256);
      WG_FENCE();
      issue_pv(Ob, P, vprev, 1); WG_COMMIT();
      pin(Oa);
      store_o_tile(qblk + 4 * BLK, 0, Oa, sa);
      WG_WAIT(0);
      pin(Ob);
      release_kv(FILL_O0 - 1);
      store_o_tile(qblk + 4 * BLK, 64, Ob, sbt);
      fence_async_smem();
      TSTAMP(4);
      if (wg == 1) named_arrive(1, 256);
      named_bar(2 + wg, 128);
    }
    TSTAMP(5);
    {
      const int t128 = tid & 127;
      const uint4* pbase = g_part + (size_t)((b * 8 + j) * 8) * (8 * 128) + t128;
      const uint32_t xch = slots + (98 % NSLOT) * SLOT_BYTES + t128 * 16;
      float sum[56];
      uint4 v[8], v2[8];
      uint32_t tagbits = 0;
#pragma unroll
      for (int i = 0; i < 8; i++) v[i] = v2[i] = make_uint4(0, 0, 0, 0);
#pragma unroll
      for (int i = 0; i < 56; i++) sum[i] = 0.f;
#pragma unroll 1
      for (int s = wg; s < 9; s += 2) {
        float acc[56];
        if (s > 0) named_bar(4 + wg, 256);
#pragma unroll
        for (int kh = 0; kh < 2; kh++) {
          if (kh == 1 && s == 0) named_bar(1, 256);
          if (kh == 1 && s >= 7) load_chunks(v2, pbase + ((j + 1 - s) & 7) * (8 * 128), 128);
#pragma unroll 1
          for (int kq = 2 * kh; kq < 2 * kh + 2; kq++) {
            const int n = FILL_O0 + s * 4 + kq;
            const uint64_t da = mkdesc(dslots + (n % NSLOT) * SLOT16), db = mkdesc(dsb + (2 * o_quarter(kq)) * BLK16);
            mbar_wait(bar_full + n * 8);
            WG_FENCE();
#pragma unroll
            for (int kk = 0; kk < 8; kk++)
              wgmma_n112_ta(acc, da + kk * 128, db + ((kk >> 2) * BLK16 + (kk & 3) * 2), kk | kq);
            WG_COMMIT();
            if (kq == 3 && s < 8) named_arrive(4 + (wg ^ 1), 256);
            if (kq > 0) { WG_WAIT(1); if (n - 1 < NFILL - NSLOT) release_both(n - 1); }
          }
        }
        if (t128 == 0) GSTAMP(1, 110 + s);
        if (s < 2) {
          mbar_wait(bar_tag);
          asm volatile("ld.shared.u32 %0, [%1];" : "=r"(tagbits) : "r"(s_tag) : "memory");
        }
        if (s >= 5) add_partial(sum, v, pbase + ((j + 4 - s) & 7) * (8 * 128), tagbits);
        if (s >= 3 && s < 8) load_chunks(v, pbase + ((j + 2 - s) & 7) * (8 * 128), 128);
        pin(sum);
        if (s == 8) {
          TSTAMP(15);
          named_bar(1, 256);
#pragma unroll
          for (int i = 0; i < 14; i++) {
            float4 t;
            asm volatile("ld.shared.v4.f32 {%0, %1, %2, %3}, [%4];" : "=f"(t.x), "=f"(t.y), "=f"(t.z), "=f"(t.w) : "r"(xch + i * 2048) : "memory");
            sum[4 * i] += t.x; sum[4 * i + 1] += t.y; sum[4 * i + 2] += t.z; sum[4 * i + 3] += t.w;
          }
          if (t128 == 0) GSTAMP(2, 110 + s);
          add_partial(sum, v2, pbase + ((j - 7) & 7) * (8 * 128), tagbits);
          WG_WAIT(0);
          pin(acc);
#pragma unroll
          for (int i = 0; i < 56; i++) sum[i] += acc[i];
          if (t128 == 0) GSTAMP(3, 110 + s);
          uint32_t pk[28];
          pack_tile(pk, sum);
          const uint32_t stg = slots + (100 % NSLOT) * SLOT_BYTES;
          store_tile_t(stg, pk, wi, lane);
          named_bar(2, 128);
          uint4* orow = reinterpret_cast<uint4*>(gout + (size_t)(b * SQ + (t128 >> 3)) * DM + j * 64) + (t128 & 7);
          const uint32_t src = stg + (t128 >> 3) * 128 + (((t128 & 7) ^ ((t128 >> 3) & 7)) << 4);
#pragma unroll
          for (int i = 0; i < 7; i++) {
            uint4 t;
            asm volatile("ld.shared.v4.u32 {%0, %1, %2, %3}, [%4];" : "=r"(t.x), "=r"(t.y), "=r"(t.z), "=r"(t.w) : "r"(src + i * 2048) : "memory");
            orow[(size_t)i * 16 * (DM / 8)] = t;
          }
          if (j == 0 && t128 == 0) atomicAdd(g_epoch + b, 1u);
        } else {
          WG_WAIT(0);
          TSTAMP(7 + (s >> 1) * 2);
          pin(acc);
          if (FILL_O0 + s * 4 + 3 < NFILL - NSLOT) release_both(FILL_O0 + s * 4 + 3);
          const float tagf = __uint_as_float(tagbits);
          if (s < 7) {
            uint4* dst = g_part + (size_t)((b * 8 + o_tile_of_step(j, s)) * 8 + j) * (8 * 128) + t128;
#pragma unroll
            for (int i = 0; i < 8; i++) store_chunk(dst + i * 128, acc + 7 * i, tagf);
          } else {
            uint4* dst = g_part8 + (size_t)(((b * 8 + 2 * wi) * 8 + j) * 4) * 32 + lane;
#pragma unroll
            for (int h = 0; h < 2; h++) {
              float e[28];
#pragma unroll
              for (int i = 0; i < 28; i++) e[i] = acc[4 * (i >> 1) + 2 * h + (i & 1)];
#pragma unroll
              for (int c = 0; c < 4; c++) store_chunk(dst + (h * 8 * 4 + c) * 32, e + 7 * c, tagf);
            }
          }
          TSTAMP(8 + (s >> 1) * 2);
          if (t128 == 0) GSTAMP(2, 110 + s);
        }
      }
      if (wg == 1) {
        const uint4* s8 = g_part8 + (size_t)(((b * 8 + j) * 8) * 4 + wi) * 32 + lane;
        add_partial(sum, v, pbase + ((j - 5) & 7) * (8 * 128), tagbits);
        add_partial(sum, v2, pbase + ((j - 6) & 7) * (8 * 128), tagbits);
        named_bar(3, 128);
#pragma unroll
        for (int i = 0; i < 14; i++)
          asm volatile("st.shared.v4.f32 [%0], {%1, %2, %3, %4};" ::"r"(xch + i * 2048), "f"(sum[4 * i]), "f"(sum[4 * i + 1]), "f"(sum[4 * i + 2]), "f"(sum[4 * i + 3]) : "memory");
        named_arrive(1, 256);
        load_chunks(v, s8, 4 * 32);
        check_chunks(v, s8, 4 * 32, tagbits);
        float r[7];
#pragma unroll
        for (int i = 0; i < 7; i++) r[i] = 0.f;
#pragma unroll
        for (int d = 0; d < 8; d++) add_chunk(r, v[d]);
        __nv_bfloat16* dst = gout + (size_t)(b * SQ + 2 * (lane & 3)) * DM + 512 + 8 * j + (lane >> 2);
#pragma unroll
        for (int i = 0; i < 7; i++) {
          const int e = 7 * wi + i;
          dst[(size_t)(8 * (e >> 1) + (e & 1)) * DM] = __float2bfloat16(r[i]);
        }
      }
    }
    TSTAMP(6);
  }
}

typedef CUresult (*EncodeFn)(CUtensorMap*, CUtensorMapDataType, cuuint32_t, void*, const cuuint64_t*, const cuuint64_t*,
                             const cuuint32_t*, const cuuint32_t*, CUtensorMapInterleave, CUtensorMapSwizzle,
                             CUtensorMapL2promotion, CUtensorMapFloatOOBfill);

void make_map(EncodeFn enc, CUtensorMap* m, const void* ptr, int rank, const cuuint64_t* dims, const cuuint64_t* strides,
              const cuuint32_t* box) {
  cuuint32_t es[3] = {1, 1, 1};
  enc(m, CU_TENSOR_MAP_DATA_TYPE_BFLOAT16, rank, const_cast<void*>(ptr), dims, strides, box, es, CU_TENSOR_MAP_INTERLEAVE_NONE,
      CU_TENSOR_MAP_SWIZZLE_128B, CU_TENSOR_MAP_L2_PROMOTION_L2_256B, CU_TENSOR_MAP_FLOAT_OOB_FILL_NONE);
}

}

extern "C" void kernel_launch(void* const* d_in, const int* in_sizes, int n_in, void* d_out, int out_size) {
  (void)in_sizes; (void)n_in; (void)out_size;
  static EncodeFn enc = nullptr;
  if (!enc) {
    void* fn = nullptr;
    cudaDriverEntryPointQueryResult qr;
    cudaGetDriverEntryPoint("cuTensorMapEncodeTiled", &fn, cudaEnableDefault, &qr);
    enc = (EncodeFn)fn;
    cudaFuncSetAttribute(gqa_fused_kernel, cudaFuncAttributeMaxDynamicSharedMemorySize, SMEM_BYTES);
  }
  CUtensorMap tx, tk, tv, twq, two;
  {
    cuuint64_t d[2] = {DM, B_ * SQ}, s[1] = {DM * 2}; cuuint32_t bx[2] = {64, SQ};
    make_map(enc, &tx, d_in[0], 2, d, s, bx);
  }
  {
    cuuint64_t d[3] = {64, (cuuint64_t)B_ * HKV * SK, 2}, s[2] = {DH * 2, 128}; cuuint32_t bx[3] = {64, 64, 2};
    make_map(enc, &tk, d_in[1], 3, d, s, bx);
    make_map(enc, &tv, d_in[2], 3, d, s, bx);
  }
  {
    cuuint64_t d[2] = {HQ * DH, DM}, s[1] = {HQ * DH * 2}; cuuint32_t bx[2] = {64, 64};
    make_map(enc, &twq, d_in[3], 2, d, s, bx);
  }
  {
    cuuint64_t d[2] = {DM, HQ * DH}, s[1] = {DM * 2}; cuuint32_t bx[2] = {64, 64};
    make_map(enc, &two, d_in[4], 2, d, s, bx);
  }
  gqa_fused_kernel<<<128, NTHREADS, SMEM_BYTES>>>(tx, tk, tv, twq, two, (const uint8_t*)d_in[0], (const uint8_t*)d_in[1], (const uint8_t*)d_in[2],
                                                   (const uint8_t*)d_in[3], (const uint8_t*)d_in[4], (__nv_bfloat16*)d_out);
}
```

```cpp
#include <cuda_runtime.h>
#include <cuda_bf16.h>
#include <cuda.h>
#include <stdint.h>

namespace {

constexpr int B_ = 16, SQ = 112, DM = 576, HQ = 32, HKV = 16, SK = 512, DH = 128;
constexpr int NSLOT = 6;
constexpr int SLOT_BYTES = 16384;
constexpr int BLK = 112 * 128;
constexpr int NFILL_Q = 36, NFILL_KV = 32, NFILL_O = 36;
constexpr int FILL_KV0 = NFILL_Q, FILL_O0 = NFILL_Q + NFILL_KV, NFILL = FILL_O0 + NFILL_O;
constexpr int OFF_SLOTS = 8 * BLK;
constexpr int OFF_STAGE = OFF_SLOTS + NSLOT * SLOT_BYTES;
constexpr int OFF_BARS = OFF_STAGE + BLK;
constexpr int NBARS = 2 * NFILL + 9 + 1;
constexpr int SMEM_BYTES = OFF_BARS + NBARS * 8 + 64;
constexpr int NTHREADS = 384;
#define PF_ON 1
#define PF_DIST 11
#define PF_LSU 0
#define WQPF 2
#define KV_EF 0
#define PF_END 3
#define EARLYPF 1
#define P6_AT 2
#define OROLL 0
#define KSPLIT(si) ((si) == 0 ? 2 : (si) == 4 ? P6_AT : 4)
#define KVLATE 1
#define PF_Q0 8
#define PF_QS 5
#define PF_CHUNK 16384
#define PF_WO_AT 31
constexpr uint32_t SPIN_LIMIT = 1u << 22;

__device__ uint4 g_part[B_ * 8 * 8 * 8 * 128];
__device__ uint4 g_part8[B_ * 8 * 8 * 4 * 32];
__device__ uint32_t g_epoch[B_];

#define TSTAMP(i) do {} while (0)

__device__ __forceinline__ uint32_t smem_u32(const void* p) { return (uint32_t)__cvta_generic_to_shared(p); }
__device__ __forceinline__ void mbar_init(uint32_t bar, uint32_t cnt) { asm volatile("mbarrier.init.shared::cta.b64 [%0], %1;" ::"r"(bar), "r"(cnt) : "memory"); }
__device__ __forceinline__ void mbar_expect_tx(uint32_t bar, uint32_t bytes) { asm volatile("mbarrier.arrive.expect_tx.shared::cta.b64 _, [%0], %1;" ::"r"(bar), "r"(bytes) : "memory"); }
__device__ __forceinline__ void mbar_arrive_pred(uint32_t bar, bool p) { asm volatile("{\n.reg .pred p;\nsetp.ne.b32 p, %1, 0;\n@p mbarrier.arrive.shared::cta.b64 _, [%0];\n}\n" ::"r"(bar), "r"((int)p) : "memory"); }
__device__ __forceinline__ void mbar_arrive_remote_pred(uint32_t rbar, bool p) { asm volatile("{\n.reg .pred p;\nsetp.ne.b32 p, %1, 0;\n@p mbarrier.arrive.shared::cluster.b64 _, [%0];\n}\n" ::"r"(rbar), "r"((int)p) : "memory"); }
__device__ __forceinline__ void mbar_wait_sleep(uint32_t bar) {
  uint32_t done, it = 0;
  do {
    asm volatile("{\n.reg .pred p;\nmbarrier.try_wait.parity.shared::cta.b64 p, [%1], 0, %2;\nselp.u32 %0, 1, 0, p;\n}\n" : "=r"(done) : "r"(bar), "r"(100000u) : "memory");
    if (++it > 4096) break;
  } while (!done);
}
__device__ __forceinline__ void mbar_wait(uint32_t bar) {
  uint32_t done, it = 0;
  do {
    asm volatile("{\n.reg .pred p;\nmbarrier.try_wait.parity.shared::cta.b64 p, [%1], 0;\nselp.u32 %0, 1, 0, p;\n}\n" : "=r"(done) : "r"(bar) : "memory");
    if (++it > SPIN_LIMIT) break;
  } while (!done);
}
__device__ __forceinline__ uint32_t mapa(uint32_t addr, uint32_t cta) { uint32_t r; asm volatile("mapa.shared::cluster.u32 %0, %1, %2;" : "=r"(r) : "r"(addr), "r"(cta)); return r; }
__device__ __forceinline__ void tma_2d(uint32_t dst, const CUtensorMap* m, int c0, int c1, uint32_t bar) {
  asm volatile("cp.async.bulk.tensor.2d.shared::cluster.global.mbarrier::complete_tx::bytes [%0], [%1, {%3, %4}], [%2];" ::"r"(dst), "l"(m), "r"(bar), "r"(c0), "r"(c1) : "memory");
}
__device__ __forceinline__ void tma_2d_mc(uint32_t dst, const CUtensorMap* m, int c0, int c1, uint32_t bar) {
  asm volatile("cp.async.bulk.tensor.2d.shared::cluster.global.mbarrier::complete_tx::bytes.multicast::cluster [%0], [%1, {%3, %4}], [%2], %5;" ::"r"(dst), "l"(m), "r"(bar), "r"(c0), "r"(c1), "h"((uint16_t)3) : "memory");
}
__device__ __forceinline__ void tma_3d(uint32_t dst, const CUtensorMap* m, int c0, int c1, int c2, uint32_t bar) {
  asm volatile("cp.async.bulk.tensor.3d.shared::cluster.global.mbarrier::complete_tx::bytes [%0], [%1, {%3, %4, %5}], [%2];" ::"r"(dst), "l"(m), "r"(bar), "r"(c0), "r"(c1), "r"(c2) : "memory");
}
__device__ __forceinline__ void tma_3d_hint(uint32_t dst, const CUtensorMap* m, int c0, int c1, int c2, uint32_t bar, uint64_t pol) {
  asm volatile("cp.async.bulk.tensor.3d.shared::cluster.global.mbarrier::complete_tx::bytes.L2::cache_hint [%0], [%1, {%3, %4, %5}], [%2], %6;" ::"r"(dst), "l"(m), "r"(bar), "r"(c0), "r"(c1), "r"(c2), "l"(pol) : "memory");
}
__device__ __forceinline__ uint4 ld_relaxed_b128(const uint4* p) {
  uint4 v;
  asm volatile("{\n.reg .b64 l, h;\n.reg .b128 t;\nld.relaxed.gpu.global.b128 t, [%4];\nmov.b128 {l, h}, t;\n"
               "mov.b64 {%0, %1}, l;\nmov.b64 {%2, %3}, h;\n}\n" : "=r"(v.x), "=r"(v.y), "=r"(v.z), "=r"(v.w) : "l"(p) : "memory");
  return v;
}
__device__ __forceinline__ void l2_prefetch(const void* p, uint32_t bytes) { asm volatile("cp.async.bulk.prefetch.L2.global [%0], %1;" ::"l"(p), "r"(bytes) : "memory"); }
__device__ __forceinline__ void prefetch_line(const void* p) { asm volatile("prefetch.global.L2 [%0];" ::"l"(p)); }
__device__ __forceinline__ void prefetch_tmap(const CUtensorMap* m) { asm volatile("prefetch.tensormap [%0];" ::"l"(m) : "memory"); }
__device__ __forceinline__ bool elect_one() { uint32_t p; asm volatile("{\n.reg .pred p;\nelect.sync _|p, 0xffffffff;\nselp.u32 %0, 1, 0, p;\n}\n" : "=r"(p)); return p != 0; }
__device__ __forceinline__ void named_bar(int id, int n) { asm volatile("bar.sync %0, %1;" ::"r"(id), "r"(n) : "memory"); }
__device__ __forceinline__ void named_arrive(int id, int n) { asm volatile("bar.arrive %0, %1;" ::"r"(id), "r"(n) : "memory"); }
__device__ __forceinline__ void fence_async_smem() { asm volatile("fence.proxy.async.shared::cta;" ::: "memory"); }
#define WG_FENCE() asm volatile("wgmma.fence.sync.aligned;" ::: "memory")
#define WG_COMMIT() asm volatile("wgmma.commit_group.sync.aligned;" ::: "memory")
#define WG_WAIT(n) asm volatile("wgmma.wait_group.sync.aligned %0;" ::"n"(n) : "memory")
template <int N> __device__ __forceinline__ void pin(float (&d)[N]) {
#pragma unroll
  for (int i = 0; i < N; i++) asm volatile("" : "+f"(d[i])::"memory");
}
__device__ __forceinline__ uint64_t mkdesc(uint32_t lo) { return ((uint64_t)(64u | (1u << 30)) << 32) | lo; }
__device__ __forceinline__ uint32_t pack_bf16(float lo, float hi) { uint32_t r; asm("cvt.rn.bf16x2.f32 %0, %1, %2;" : "=r"(r) : "f"(hi), "f"(lo)); return r; }
__device__ __forceinline__ float ex2(float x) { float r; asm("ex2.approx.ftz.f32 %0, %1;" : "=f"(r) : "f"(x)); return r; }
__device__ __forceinline__ float rcp_fast(float x) { float r; asm("rcp.approx.ftz.f32 %0, %1;" : "=f"(r) : "f"(x)); return r; }
__device__ __forceinline__ void stsm_x4(uint32_t addr, uint32_t r0, uint32_t r1, uint32_t r2, uint32_t r3) {
  asm volatile("stmatrix.sync.aligned.m8n8.x4.shared.b16 [%0], {%1, %2, %3, %4};" ::"r"(addr), "r"(r0), "r"(r1), "r"(r2), "r"(r3) : "memory");
}
__device__ __forceinline__ void stsm_x4_t(uint32_t addr, uint32_t r0, uint32_t r1, uint32_t r2, uint32_t r3) {
  asm volatile("stmatrix.sync.aligned.m8n8.x4.trans.shared.b16 [%0], {%1, %2, %3, %4};" ::"r"(addr), "r"(r0), "r"(r1), "r"(r2), "r"(r3) : "memory");
}

__device__ __forceinline__ void wgmma_n112_ta(float (&d)[56], uint64_t da, uint64_t db, int sc) {
  asm volatile("{\n.reg .pred p;\nsetp.ne.b32 p, %58, 0;\n"
    "wgmma.mma_async.sync.aligned.m64n112k16.f32.bf16.bf16 "
    "{%0, %1, %2, %3, %4, %5, %6, %7, %8, %9, %10, %11, %12, %13, %14, %15, %16, %17, %18, %19, %20, %21, %22, %23, %24, %25, %26, %27, %28, %29, %30, %31, %32, %33, %34, %35, %36, %37, %38, %39, %40, %41, %42, %43, %44, %45, %46, %47, %48, %49, %50, %51, %52, %53, %54, %55}, "
    "%56, %57, p, 1, 1, 1, 0;\n}\n"
    : "+f"(d[0]), "+f"(d[1]), "+f"(d[2]), "+f"(d[3]), "+f"(d[4]), "+f"(d[5]), "+f"(d[6]), "+f"(d[7]), "+f"(d[8]), "+f"(d[9]), "+f"(d[10]), "+f"(d[11]), "+f"(d[12]), "+f"(d[13]), "+f"(d[14]), "+f"(d[15]), "+f"(d[16]), "+f"(d[17]), "+f"(d[18]), "+f"(d[19]), "+f"(d[20]), "+f"(d[21]), "+f"(d[22]), "+f"(d[23]), "+f"(d[24]), "+f"(d[25]), "+f"(d[26]), "+f"(d[27]), "+f"(d[28]), "+f"(d[29]), "+f"(d[30]), "+f"(d[31]), "+f"(d[32]), "+f"(d[33]), "+f"(d[34]), "+f"(d[35]), "+f"(d[36]), "+f"(d[37]), "+f"(d[38]), "+f"(d[39]), "+f"(d[40]), "+f"(d[41]), "+f"(d[42]), "+f"(d[43]), "+f"(d[44]), "+f"(d[45]), "+f"(d[46]), "+f"(d[47]), "+f"(d[48]), "+f"(d[49]), "+f"(d[50]), "+f"(d[51]), "+f"(d[52]), "+f"(d[53]), "+f"(d[54]), "+f"(d[55])
    : "l"(da), "l"(db), "r"(sc));
}

__device__ __forceinline__ void wgmma_n64_ss(float (&d)[32], uint64_t da, uint64_t db, int sc) {
  asm volatile("{\n.reg .pred p;\nsetp.ne.b32 p, %34, 0;\n"
    "wgmma.mma_async.sync.aligned.m64n64k16.f32.bf16.bf16 "
    "{%0, %1, %2, %3, %4, %5, %6, %7, %8, %9, %10, %11, %12, %13, %14, %15, %16, %17, %18, %19, %20, %21, %22, %23, %24, %25, %26, %27, %28, %29, %30, %31}, "
    "%32, %33, p, 1, 1, 0, 0;\n}\n"
    : "+f"(d[0]), "+f"(d[1]), "+f"(d[2]), "+f"(d[3]), "+f"(d[4]), "+f"(d[5]), "+f"(d[6]), "+f"(d[7]), "+f"(d[8]), "+f"(d[9]), "+f"(d[10]), "+f"(d[11]), "+f"(d[12]), "+f"(d[13]), "+f"(d[14]), "+f"(d[15]), "+f"(d[16]), "+f"(d[17]), "+f"(d[18]), "+f"(d[19]), "+f"(d[20]), "+f"(d[21]), "+f"(d[22]), "+f"(d[23]), "+f"(d[24]), "+f"(d[25]), "+f"(d[26]), "+f"(d[27]), "+f"(d[28]), "+f"(d[29]), "+f"(d[30]), "+f"(d[31])
    : "l"(da), "l"(db), "r"(sc));
}

__device__ __forceinline__ void wgmma_n128_rs(float (&d)[64], uint32_t a0, uint32_t a1, uint32_t a2, uint32_t a3, uint64_t db, int sc) {
  asm volatile("{\n.reg .pred p;\nsetp.ne.b32 p, %69, 0;\n"
    "wgmma.mma_async.sync.aligned.m64n128k16.f32.bf16.bf16 "
    "{%0, %1, %2, %3, %4, %5, %6, %7, %8, %9, %10, %11, %12, %13, %14, %15, %16, %17, %18, %19, %20, %21, %22, %23, %24, %25, %26, %27, %28, %29, %30, %31, %32, %33, %34, %35, %36, %37, %38, %39, %40, %41, %42, %43, %44, %45, %46, %47, %48, %49, %50, %51, %52, %53, %54, %55, %56, %57, %58, %59, %60, %61, %62, %63}, "
    "{%64, %65, %66, %67}, %68, p, 1, 1, 1;\n}\n"
    : "+f"(d[0]), "+f"(d[1]), "+f"(d[2]), "+f"(d[3]), "+f"(d[4]), "+f"(d[5]), "+f"(d[6]), "+f"(d[7]), "+f"(d[8]), "+f"(d[9]), "+f"(d[10]), "+f"(d[11]), "+f"(d[12]), "+f"(d[13]), "+f"(d[14]), "+f"(d[15]), "+f"(d[16]), "+f"(d[17]), "+f"(d[18]), "+f"(d[19]), "+f"(d[20]), "+f"(d[21]), "+f"(d[22]), "+f"(d[23]), "+f"(d[24]), "+f"(d[25]), "+f"(d[26]), "+f"(d[27]), "+f"(d[28]), "+f"(d[29]), "+f"(d[30]), "+f"(d[31]), "+f"(d[32]), "+f"(d[33]), "+f"(d[34]), "+f"(d[35]), "+f"(d[36]), "+f"(d[37]), "+f"(d[38]), "+f"(d[39]), "+f"(d[40]), "+f"(d[41]), "+f"(d[42]), "+f"(d[43]), "+f"(d[44]), "+f"(d[45]), "+f"(d[46]), "+f"(d[47]), "+f"(d[48]), "+f"(d[49]), "+f"(d[50]), "+f"(d[51]), "+f"(d[52]), "+f"(d[53]), "+f"(d[54]), "+f"(d[55]), "+f"(d[56]), "+f"(d[57]), "+f"(d[58]), "+f"(d[59]), "+f"(d[60]), "+f"(d[61]), "+f"(d[62]), "+f"(d[63])
    : "r"(a0), "r"(a1), "r"(a2), "r"(a3), "l"(db), "r"(sc));
}

template <int I0 = 0, int I1 = 7>
__device__ __forceinline__ void store_tile_t(uint32_t blk, const uint32_t (&pk)[28], int wi, int lane) {
  const int mi = lane >> 3, r = lane & 7;
  const uint32_t base = blk + (uint32_t)(((mi >> 1) * 8 + r) * 128 + (((2 * wi + (mi & 1)) ^ r) << 4));
#pragma unroll
  for (int i = I0; i < I1; i++) stsm_x4_t(base + i * 2048, pk[4 * i], pk[4 * i + 1], pk[4 * i + 2], pk[4 * i + 3]);
}
__device__ __forceinline__ void pack_tile(uint32_t (&pk)[28], const float (&a)[56]) {
#pragma unroll
  for (int i = 0; i < 28; i++) pk[i] = pack_bf16(a[2 * i], a[2 * i + 1]);
}

constexpr float SCALE_LOG2E = 0.08838834764831845f * 1.4426950408889634f;
__device__ __forceinline__ void pack_tile_scaled(uint32_t (&pk)[28], const float (&a)[56]) {
#pragma unroll
  for (int i = 0; i < 28; i++) pk[i] = pack_bf16(a[2 * i] * SCALE_LOG2E, a[2 * i + 1] * SCALE_LOG2E);
}

struct RowStat { float m0, m1, l0, l1; };

__device__ __forceinline__ void finish_rows(RowStat& st) {
  float l0 = st.l0, l1 = st.l1;
  l0 += __shfl_xor_sync(0xffffffffu, l0, 1); l1 += __shfl_xor_sync(0xffffffffu, l1, 1);
  l0 += __shfl_xor_sync(0xffffffffu, l0, 2); l1 += __shfl_xor_sync(0xffffffffu, l1, 2);
  st.l0 = rcp_fast(l0); st.l1 = rcp_fast(l1);
}
__device__ __forceinline__ void store_o_tile(uint32_t blk0, int row0, float (&O)[64], const RowStat& st) {
  int tid_;
  asm volatile("mov.u32 %0, %%tid.x;" : "=r"(tid_));
  const int lane = tid_ & 31, wi = (tid_ >> 5) & 3;
  const float i0 = st.l0, i1 = st.l1;
  const int mi = lane >> 3, r = lane & 7;
  const uint32_t base = blk0 + (uint32_t)((row0 + 16 * wi + (mi & 1) * 8 + r) * 128);
#pragma unroll
  for (int i = 0; i < 16; i += 2) {
    const int cg = (i & 7) + (mi >> 1);
    const uint32_t addr = base + (uint32_t)((i >> 3) * BLK) + (uint32_t)((cg ^ r) << 4);
    const uint32_t w0 = pack_bf16(O[4 * i] * i0, O[4 * i + 1] * i0), w1 = pack_bf16(O[4 * i + 2] * i1, O[4 * i + 3] * i1);
    const uint32_t w2 = pack_bf16(O[4 * i + 4] * i0, O[4 * i + 5] * i0), w3 = pack_bf16(O[4 * i + 6] * i1, O[4 * i + 7] * i1);
    stsm_x4(addr, w0, w1, w2, w3);
  }
}

constexpr float SUM_HI = 16777216.0f, SUM_HI_LOG2 = 24.0f, SUM_LO = 1.0f / 16777216.0f;
__device__ __forceinline__ void sub_ref(float (&S)[32], const RowStat& st) {
#pragma unroll
  for (int i = 0; i < 8; i++) { S[4 * i] -= st.m0; S[4 * i + 1] -= st.m0; S[4 * i + 2] -= st.m1; S[4 * i + 3] -= st.m1; }
}
__device__ __forceinline__ void update_ref(float (&T)[32], float (&O)[64], RowStat& st, bool first) {
  float a0 = fmaxf(T[0], T[1]), a1 = fmaxf(T[2], T[3]), b0 = fmaxf(T[4], T[5]), b1 = fmaxf(T[6], T[7]);
#pragma unroll
  for (int i = 2; i < 8; i += 2) {
    a0 = fmaxf(a0, fmaxf(T[4 * i], T[4 * i + 1])); a1 = fmaxf(a1, fmaxf(T[4 * i + 2], T[4 * i + 3]));
    b0 = fmaxf(b0, fmaxf(T[4 * i + 4], T[4 * i + 5])); b1 = fmaxf(b1, fmaxf(T[4 * i + 6], T[4 * i + 7]));
  }
  float d0 = fmaxf(a0, b0), d1 = fmaxf(a1, b1);
  d0 = fmaxf(d0, __shfl_xor_sync(0xffffffffu, d0, 1)); d1 = fmaxf(d1, __shfl_xor_sync(0xffffffffu, d1, 1));
  d0 = fmaxf(d0, __shfl_xor_sync(0xffffffffu, d0, 2)); d1 = fmaxf(d1, __shfl_xor_sync(0xffffffffu, d1, 2));
  if (first) {
    st.m0 = d0; st.m1 = d1;
  } else {
    d0 = fmaxf(d0, 0.f); d1 = fmaxf(d1, 0.f);
    const float r0 = ex2(-d0), r1 = ex2(-d1);
    st.m0 += d0; st.m1 += d1; st.l0 *= r0; st.l1 *= r1;
#pragma unroll
    for (int i = 0; i < 16; i++) { O[4 * i] *= r0; O[4 * i + 1] *= r0; O[4 * i + 2] *= r1; O[4 * i + 3] *= r1; }
  }
#pragma unroll
  for (int i = 0; i < 8; i++) { T[4 * i] -= d0; T[4 * i + 1] -= d0; T[4 * i + 2] -= d1; T[4 * i + 3] -= d1; }
}
__device__ __forceinline__ bool softmax_exp(const float (&T)[32], uint32_t (&P)[16], float& l0, float& l1, float lo) {
  const bool ok_last = fmaxf(fmaxf(T[28], T[29]), fmaxf(T[30], T[31])) <= SUM_HI_LOG2;
  bool bad = false;
#pragma unroll
  for (int i = 0; i < 8; i++) {
    if (i == 7) bad = __any_sync(0xffffffffu, !(fmaxf(l0, l1) <= SUM_HI && fminf(l0, l1) >= lo && ok_last));
    const float p0 = ex2(T[4 * i]), p1 = ex2(T[4 * i + 1]), p2 = ex2(T[4 * i + 2]), p3 = ex2(T[4 * i + 3]);
    if (i == 0) { l0 = p0; l1 = p2; } else { l0 += p0; l1 += p2; }
    l0 += p1; l1 += p3;
    P[2 * i] = pack_bf16(p0, p1); P[2 * i + 1] = pack_bf16(p2, p3);
  }
  return bad;
}
__device__ __forceinline__ void softmax_tile(float (&T)[32], float (&O)[64], uint32_t (&P)[16], RowStat& st, bool& sub, bool first) {
  float l0, l1;
  if (__builtin_expect(softmax_exp(T, P, l0, l1, first ? SUM_LO : 0.f), 0)) {
    update_ref(T, O, st, first);
    sub = true;
    softmax_exp(T, P, l0, l1, 0.f);
  }
  st.l0 += l0; st.l1 += l1;
}

__device__ __forceinline__ void issue_s(float (&S)[32], uint32_t q16, uint32_t k16) {
  const uint64_t dq = mkdesc(q16), dk = mkdesc(k16);
#pragma unroll
  for (int kk = 0; kk < 8; kk++)
    wgmma_n64_ss(S, dq + ((kk >> 2) * (BLK / 16) + (kk & 3) * 2), dk + ((kk >> 2) * 512 + (kk & 3) * 2), kk != 0);
}
__device__ __forceinline__ void issue_pv(float (&O)[64], const uint32_t (&P)[16], uint32_t v16, int acc) {
  const uint64_t dv = mkdesc(v16 + (512u << 16));
#pragma unroll
  for (int kk = 0; kk < 4; kk++)
    wgmma_n128_rs(O, P[4 * kk], P[4 * kk + 1], P[4 * kk + 2], P[4 * kk + 3], dv + kk * 128, kk ? 1 : acc);
}

__device__ __forceinline__ int o_tile_of_step(int j, int s) { return s == 7 ? 8 : ((j + 1 + s - (s == 8)) & 7); }
__device__ __forceinline__ int o_quarter(int kq) { return ((kq & 1) << 1) | (kq >> 1); }

__device__ __forceinline__ void store_chunk(uint4* p, const float* a, float tagf) {
  asm volatile("st.relaxed.gpu.global.v4.b32 [%0], {%1, %2, %3, %4};" ::"l"(p), "r"(pack_bf16(a[0], a[1])),
               "r"(pack_bf16(a[2], a[3])), "r"(pack_bf16(a[4], a[5])), "r"(pack_bf16(a[6], tagf)) : "memory");
}
__device__ __forceinline__ void add_chunk(float* a, const uint4& v) {
  a[0] += __uint_as_float(v.x << 16); a[1] += __uint_as_float(v.x & 0xffff0000u);
  a[2] += __uint_as_float(v.y << 16); a[3] += __uint_as_float(v.y & 0xffff0000u);
  a[4] += __uint_as_float(v.z << 16); a[5] += __uint_as_float(v.z & 0xffff0000u);
  a[6] += __uint_as_float(v.w << 16);
}
__device__ __forceinline__ void load_chunks(uint4 (&v)[8], const uint4* p, int stride) {
#pragma unroll
  for (int i = 0; i < 8; i++) v[i] = ld_relaxed_b128(p + i * stride);
}
__device__ __forceinline__ void check_chunks(uint4 (&v)[8], const uint4* p, int stride, uint32_t tagbits) {
  uint32_t it = 0;
  for (;;) {
    uint32_t bad = 0;
#pragma unroll
    for (int i = 0; i < 8; i++) bad |= v[i].w ^ tagbits;
    if (!__any_sync(0xffffffffu, bad > 0xffffu) || ++it > SPIN_LIMIT) break;
    load_chunks(v, p, stride);
  }
}
__device__ __forceinline__ void add_partial(float (&a)[56], uint4 (&v)[8], const uint4* p, uint32_t tagbits) {
  check_chunks(v, p, 128, tagbits);
#pragma unroll
  for (int i = 0; i < 8; i++) add_chunk(a + 7 * i, v[i]);
}

__host__ __device__ constexpr uint32_t bar_count(int i) {
  return i >= 2 * NFILL ? 1
       : i >= NFILL ? ((i - NFILL >= FILL_O0 - NSLOT && i - NFILL < FILL_O0) ? 16 : 8)
       : (i > FILL_KV0 && i < FILL_O0 - 1) ? 2 : 1;
}
template <int W> __device__ __forceinline__ void init_barriers(uint32_t base, int w) {
  constexpr int NW = NTHREADS / 32 - 1, PER = (NBARS + NW - 1) / NW;
  if (w == W) {
#pragma unroll
    for (int i = W * PER; i < (W + 1) * PER && i < NBARS; i++)
      if (i > 1 && i != 2 * NFILL && i != 2 * NFILL + 1) mbar_init(base + i * 8, bar_count(i));
  } else if constexpr (W + 1 < NW) {
    init_barriers<W + 1>(base, w);
  }
}

__global__ void __cluster_dims__(2, 1, 1) __launch_bounds__(NTHREADS, 1)
gqa_fused_kernel(const __grid_constant__ CUtensorMap tm_x, const __grid_constant__ CUtensorMap tm_k,
                 const __grid_constant__ CUtensorMap tm_v, const __grid_constant__ CUtensorMap tm_wq,
                 const __grid_constant__ CUtensorMap tm_wo, const uint8_t* __restrict__ gx,
                 const uint8_t* __restrict__ gk, const uint8_t* __restrict__ gv, const uint8_t* __restrict__ gwq,
                 const uint8_t* __restrict__ gwo, __nv_bfloat16* __restrict__ gout) {
  extern __shared__ __align__(1024) uint8_t smem[];
  const uint32_t sb = smem_u32(smem);
  const uint32_t slots = sb + OFF_SLOTS;
  const uint32_t bar_full = sb + OFF_BARS, bar_empty = bar_full + NFILL * 8, bar_x = bar_empty + NFILL * 8, bar_tag = bar_x + 9 * 8,
                 s_tag = bar_tag + 8, stage = sb + OFF_STAGE;
  const int tid = threadIdx.x, lane = tid & 31;
  const int wg = __shfl_sync(0xffffffffu, tid >> 7, 0), wi = __shfl_sync(0xffffffffu, (tid >> 5) & 3, 0);
  const uint32_t rank = blockIdx.x & 1;
  const int cl = blockIdx.x >> 1;
  const int j = cl & 7, b = (cl >> 3) * 2 + (int)rank;

  TSTAMP(0);
  if (tid < 32) prefetch_line(gwq + (size_t)(64 + b * 8 + (tid >> 2)) * (HQ * DH * 2) + j * 1024 + (tid & 3) * 128);
  else if (tid < 60) prefetch_line(gx + (size_t)(b * SQ + j * 14 + ((tid - 32) >> 1)) * (DM * 2) + 256 + (tid & 1) * 128);
  if (tid == 256) {
    mbar_init(bar_full, 1); mbar_init(bar_full + 8, 1); mbar_init(bar_x, 1); mbar_init(bar_x + 8, 1);
    asm volatile("fence.mbarrier_init.release.cluster;" ::: "memory");
    fence_async_smem();
    mbar_expect_tx(bar_x, BLK);
    tma_2d(sb, &tm_x, 0, b * SQ, bar_x);
#pragma unroll
    for (int w = 0; w < 2; w++) {
      mbar_expect_tx(bar_full + w * 8, SLOT_BYTES);
      tma_2d(slots + w * SLOT_BYTES, &tm_wq, (4 * j + w) * DH, 0, bar_full + w * 8);
      tma_2d(slots + w * SLOT_BYTES + 8192, &tm_wq, (4 * j + w) * DH + 64, 0, bar_full + w * 8);
    }
    mbar_expect_tx(bar_x + 8, BLK);
    tma_2d(sb + BLK, &tm_x, 64, b * SQ, bar_x + 8);
  } else if (lane == 0) {
    init_barriers<0>(bar_full, wg * 4 + wi - (wg == 2));
    asm volatile("fence.mbarrier_init.release.cluster;" ::: "memory");
    if (tid == 288) { prefetch_tmap(&tm_k); prefetch_tmap(&tm_v); prefetch_tmap(&tm_wo); }
  }
  __syncwarp();
  __syncthreads();
  asm volatile("barrier.cluster.arrive.relaxed.aligned;" ::: "memory");
  __syncwarp();
  asm volatile("barrier.cluster.wait.acquire.aligned;" ::: "memory");

  if (wg == 2) {
    asm volatile("setmaxnreg.dec.sync.aligned.u32 24;");
    if (wi < 2) {
      const uint32_t slot0 = slots + wi * SLOT_BYTES;
      uint32_t dst = slot0, fb = bar_full + wi * 8;
      auto next = [&]() { dst = (dst == slot0 + 4 * SLOT_BYTES) ? slot0 : dst + 2 * SLOT_BYTES; fb += 16; };
      constexpr uint32_t EMPTY_OFF = NFILL * 8 - NSLOT * 8;
      int c0 = (4 * j + wi) * DH + (int)rank * 64;
      next();
#pragma unroll 1
      for (int t = 1; t < 18; t++) {
        const int k = t < 9 ? t : t - 9;
        if (t == 9) c0 += 2 * DH;
        if (t >= 3) mbar_wait_sleep(fb + EMPTY_OFF);
        if (elect_one()) {
          mbar_expect_tx(fb, SLOT_BYTES);
          tma_2d_mc(dst + rank * 8192, &tm_wq, c0, k * 64, fb);
          if (t < 8 && wi == 1) {
            mbar_expect_tx(bar_x + (t + 1) * 8, BLK);
            tma_2d(t < 7 ? sb + (t + 1) * BLK : stage, &tm_x, (t + 1) * 64, b * SQ, bar_x + (t + 1) * 8);
          }
        }
        next();
      }
      const CUtensorMap* tm_kv = wi ? &tm_v : &tm_k;
      uint64_t pol;
      asm volatile("createpolicy.fractional.L2::evict_first.b64 %0, 1.0;" : "=l"(pol));
      int row = (b * HKV + 2 * j) * SK;
#pragma unroll 1
      for (int t = 0; t < 16; t++) {
        mbar_wait_sleep(fb + EMPTY_OFF + ((wi && t >= 3) ? 8 : 0));
        const uint32_t f = fb - ((!wi && t > 0) ? 8 : 0);
        if (elect_one()) {
          mbar_expect_tx(f, SLOT_BYTES);
          tma_3d(dst, tm_kv, 0, row, 0, f);
        }
        row += 64;
        next();
      }
      const int r0 = j * 512 + wi * 256 + (int)rank * 64;
#pragma unroll 1
      for (int t = 0; t < 18; t++) {
        mbar_wait_sleep(fb + EMPTY_OFF + ((wi && t < 2) ? 8 : 0));
        const int cw = o_tile_of_step(j, t >> 1) * 64;
        if (elect_one()) {
          mbar_expect_tx(fb, SLOT_BYTES);
          tma_2d_mc(dst + rank * 8192, &tm_wo, cw, r0 + (t & 1) * 128, fb);
        }
        next();
      }
    } else if (wi == 2) {
      const size_t kv0 = (size_t)(b * HKV + 2 * j) * SK * DH * 2;
#pragma unroll 1
      for (int c = 0; c < (PF_ON ? 32 : 0); c++) {
        mbar_wait_sleep(bar_full + (c < PF_DIST ? PF_Q0 + (c * PF_QS) / 2 : FILL_KV0 + (((c - PF_DIST) * (31 - PF_END) / (31 - PF_DIST)) | 1)) * 8);
        const uint8_t* p = ((c & 1) ? gv : gk) + kv0 + (size_t)(c >> 1) * 16384;
        if (lane < 16384 / PF_CHUNK) l2_prefetch(p + lane * PF_CHUNK, PF_CHUNK);
        if (c == PF_WO_AT && lane < 18) l2_prefetch(gwo + (size_t)j * (512 * DM * 2) + (size_t)b * 36864 + lane * 2048, 2048);
      }
    } else if (wi == 3) {
      const uint8_t* wq0 = gwq + (size_t)b * (HQ * DH * 2) + j * 1024 + (lane & 3) * 128;
#pragma unroll
      for (int i = 0; i < 3; i++) prefetch_line(wq0 + (size_t)(192 + 16 * (i * 8 + (lane >> 2))) * (HQ * DH * 2));
      if ((lane & 15) < 14) {
        const uint8_t* xr = gx + (size_t)(b * SQ + j * 14 + (lane & 15)) * (DM * 2) + (4 + (lane >> 4)) * 128;
        prefetch_line(xr); prefetch_line(xr + 256);
        if (lane < 16) prefetch_line(xr + 512);
      }
      mbar_wait_sleep(bar_full + 2 * 8);
#pragma unroll
      for (int i = 0; i < 5; i++)
        if (i * 8 + (lane >> 2) < 36) prefetch_line(wq0 + 512 + (size_t)(16 * (i * 8 + (lane >> 2))) * (HQ * DH * 2));
      if (lane == 0) {
        const uint32_t e = *reinterpret_cast<volatile uint32_t*>(g_epoch + b);
        asm volatile("st.shared.u32 [%0], %1;" ::"r"(s_tag), "r"((0x0800u + e % 0x7000u) << 16) : "memory");
        mbar_arrive_pred(bar_tag, true);
      }
    }
  } else {
    asm volatile("setmaxnreg.inc.sync.aligned.u32 240;");
    const uint32_t peer_empty = mapa(bar_empty, rank ^ 1);
    const uint32_t dsb = (sb & 0x3FFFF) >> 4, dslots = dsb + OFF_SLOTS / 16;
    constexpr uint32_t BLK16 = BLK / 16, SLOT16 = SLOT_BYTES / 16;
    auto release_both = [&](int n) { mbar_arrive_pred(bar_empty + n * 8, lane == 0); mbar_arrive_remote_pred(peer_empty + n * 8, lane == 0); };
    auto release_kv = [&](int n) {
      mbar_arrive_pred(bar_empty + n * 8, lane == 0);
      mbar_arrive_remote_pred(peer_empty + n * 8, lane == 0 && n >= FILL_O0 - NSLOT);
    };
    TSTAMP(1);
    const uint32_t qblk = sb + (2 * wg) * BLK, dq = dsb + (2 * wg) * BLK16;
    float Sa[32];
    {
      float acc0[56], acc1[56];
      uint32_t q0[28], q1[28];
      if (wg == 1) named_arrive(4, 256);
      auto q_step = [&](int n, int k) {
        const uint64_t da = mkdesc(dslots + (n % NSLOT) * SLOT16), db = mkdesc(dsb + (k < 8 ? k * BLK16 : OFF_STAGE / 16));
        mbar_wait(bar_full + n * 8);
        named_bar(4 + wg, 256);
        WG_FENCE();
#pragma unroll
        for (int kk = 0; kk < 4; kk++) {
          wgmma_n112_ta(acc0, da + kk * 128, db + kk * 2, (k | kk) != 0);
          wgmma_n112_ta(acc1, da + (512 + kk * 128), db + kk * 2, (k | kk) != 0);
        }
        WG_COMMIT();
        named_arrive(4 + (wg ^ 1), 256);
        if (k > 0) { WG_WAIT(1); release_both(n - 2); }
      };
#pragma unroll 1
      for (int k = 0; k < 9; k++) {
        mbar_wait(bar_x + k * 8);
        q_step(k * 2 + wg, k);
      }
      WG_WAIT(0);
      release_both(16 + wg);
      pin(acc0); pin(acc1);
      pack_tile_scaled(q0, acc0); pack_tile_scaled(q1, acc1);
#pragma unroll 1
      for (int k = 0; k < 9; k++) {
        q_step(18 + k * 2 + wg, k);
        if (k == 4 + wg) store_tile_t<0, 4>(qblk, q0, wi, lane);
        if (k == 5 + wg) store_tile_t<4, 7>(qblk, q0, wi, lane);
        if (k == 6 + wg) store_tile_t<0, 4>(qblk + BLK, q1, wi, lane);
        if (k == 7 + wg) store_tile_t<4, 7>(qblk + BLK, q1, wi, lane);
      }
      TSTAMP(2);
      WG_WAIT(0);
      release_both(34 + wg);
      fence_async_smem();
      mbar_wait(bar_full + FILL_KV0 * 8);
      named_bar(4 + wg, 256);
      WG_FENCE();
      issue_s(Sa, dq, dslots + (FILL_KV0 % NSLOT) * SLOT16);
      WG_COMMIT();
      named_arrive(4 + (wg ^ 1), 256);
      pin(acc0); pin(acc1);
      pack_tile_scaled(q0, acc0); pack_tile_scaled(q1, acc1);
      store_tile_t(qblk + 4 * BLK, q0, wi, lane);
      store_tile_t(qblk + 5 * BLK, q1, wi, lane);
    }
    TSTAMP(3);
    {
      float Oa[64], Ob[64], Sb[32];
      uint32_t P[16];
      RowStat sa, sbt;
      WG_WAIT(0);
      fence_async_smem();
#pragma unroll
      for (int i = 0; i < 64; i++) { Oa[i] = 0.f; Ob[i] = 0.f; }
#pragma unroll
      for (int i = 0; i < 16; i++) P[i] = 0u;
      sa.m0 = sa.m1 = sbt.m0 = sbt.m1 = 0.f; sa.l0 = sa.l1 = sbt.l0 = sbt.l1 = 0.f;
      int slot_k = FILL_KV0 % NSLOT;
      bool suba = false, subb = false;
      pin(Oa); pin(Ob);
      uint32_t vprev = dslots + slot_k * SLOT16;
#pragma unroll 1
      for (int jj = 0; jj < 16; jj++) {
        const int nk = FILL_KV0 + 2 * jj;
        const uint32_t kcur = dslots + slot_k * SLOT16, vaddr = kcur + SLOT16;
        slot_k = (slot_k == NSLOT - 2) ? 0 : slot_k + 2;
        const uint32_t knext = dslots + slot_k * SLOT16;
        const bool first = (jj & 7) == 0;
        if (jj == 1) TSTAMP(8); if (jj == 8) TSTAMP(10); if (jj == 10) TSTAMP(12); if (jj == 15) TSTAMP(14);
        named_bar(4 + wg, 256);
        WG_FENCE();
        issue_pv(Ob, P, vprev, (jj & 7) != 1);
        WG_COMMIT();
        issue_s(Sb, dq + (jj >= 8 ? 4 * BLK16 : 0) + 512, kcur);
        WG_COMMIT();
        named_arrive(4 + (wg ^ 1), 256);
        if (jj == 8) finish_rows(sa);
        WG_WAIT(1);
        pin(Oa); pin(Sa);
        if (__builtin_expect(jj == 8 || suba, 0)) {
          if (jj == 8) {
            store_o_tile(qblk, 0, Oa, sa);
            sa.m0 = sa.m1 = sa.l0 = sa.l1 = 0.f; suba = false;
          } else {
            sub_ref(Sa, sa);
          }
        }
        softmax_tile(Sa, Oa, P, sa, suba, first);
        mbar_wait(bar_full + (nk + 1) * 8);
        WG_WAIT(0);
        release_kv(nk);
        named_bar(4 + wg, 256);
        WG_FENCE();
        issue_pv(Oa, P, vaddr, !first);
        WG_COMMIT();
        issue_s(Sa, dq + (jj >= 7 ? 4 * BLK16 : 0), knext);
        WG_COMMIT();
        named_arrive(4 + (wg ^ 1), 256);
        if (jj == 8) finish_rows(sbt);
        WG_WAIT(1);
        pin(Ob); pin(Sb);
        if (wi < 3) {
          if (__builtin_expect(jj == 8 || subb, 0)) {
            if (jj == 8) {
              store_o_tile(qblk, 64, Ob, sbt);
              sbt.m0 = sbt.m1 = sbt.l0 = sbt.l1 = 0.f; subb = false;
            } else {
              sub_ref(Sb, sbt);
            }
          }
          softmax_tile(Sb, Ob, P, sbt, subb, first);
        }
        WG_WAIT(0);
        vprev = vaddr;
      }
      if (wg == 0) named_bar(4, 256);
      WG_FENCE();
      issue_pv(Ob, P, vprev, 1); WG_COMMIT();
      pin(Oa);
      finish_rows(sa); finish_rows(sbt);
      store_o_tile(qblk + 4 * BLK, 0, Oa, sa);
      WG_WAIT(0);
      pin(Ob);
      release_kv(FILL_O0 - 1);
      if (wi < 3) store_o_tile(qblk + 4 * BLK, 64, Ob, sbt);
      fence_async_smem();
      TSTAMP(4);
      if (wg == 1) named_arrive(1, 256);
      named_bar(2 + wg, 128);
    }
    TSTAMP(5);
    {
      const int t128 = tid & 127;
      const uint4* pbase = g_part + (size_t)((b * 8 + j) * 8) * (8 * 128) + t128;
      const uint32_t xch = slots + (98 % NSLOT) * SLOT_BYTES + t128 * 16;
      float sum[56];
      uint4 v[8], v2[8];
      uint32_t tagbits = 0;
#pragma unroll
      for (int i = 0; i < 8; i++) v[i] = v2[i] = make_uint4(0, 0, 0, 0);
#pragma unroll
      for (int i = 0; i < 56; i++) sum[i] = 0.f;
#pragma unroll
      for (int si = 0; si < 5; si++) {
        const int s = 2 * si + (wg & 1);
        if (s > 8) break;
        float acc[56];
        if (s == 8) { add_partial(sum, v, pbase + ((j - 4) & 7) * (8 * 128), tagbits); pin(sum); }
        if (s > 0) named_bar(4 + wg, 256);
#pragma unroll
        for (int kh = 0; kh < 2; kh++) {
          if (kh == 1 && s == 0) named_bar(1, 256);
          if (kh == 1 && s == 8) load_chunks(v, pbase + ((j - 7) & 7) * (8 * 128), 128);
#pragma unroll 1
          for (int kq = (kh ? KSPLIT(si) : 0); kq < (kh ? 4 : KSPLIT(si)); kq++) {
            const int n = FILL_O0 + s * 4 + kq;
            const uint64_t da = mkdesc(dslots + (n % NSLOT) * SLOT16), db = mkdesc(dsb + (2 * o_quarter(kq)) * BLK16);
            mbar_wait(bar_full + n * 8);
            WG_FENCE();
#pragma unroll
            for (int kk = 0; kk < 8; kk++)
              wgmma_n112_ta(acc, da + kk * 128, db + ((kk >> 2) * BLK16 + (kk & 3) * 2), kk | kq);
            WG_COMMIT();
            if (kq == 3 && s < 8) named_arrive(4 + (wg ^ 1), 256);
            if (kq > 0) { WG_WAIT(1); if (n - 1 < NFILL - NSLOT) release_both(n - 1); }
          }
        }
        if (s < 2) {
          mbar_wait(bar_tag);
          asm volatile("ld.shared.u32 %0, [%1];" : "=r"(tagbits) : "r"(s_tag) : "memory");
        }
        if (s >= 5 && s < 8) add_partial(sum, v, pbase + ((j + 4 - s) & 7) * (8 * 128), tagbits);
        if (s >= 3 && s < 8) load_chunks(v, pbase + ((j + 2 - s) & 7) * (8 * 128), 128);
        if (s == 7) load_chunks(v2, pbase + ((j - 6) & 7) * (8 * 128), 128);
        pin(sum);
        if (s == 8) {
          TSTAMP(15);
          named_bar(1, 256);
#pragma unroll
          for (int i = 0; i < 14; i++) {
            float4 t;
            asm volatile("ld.shared.v4.f32 {%0, %1, %2, %3}, [%4];" : "=f"(t.x), "=f"(t.y), "=f"(t.z), "=f"(t.w) : "r"(xch + i * 2048) : "memory");
            sum[4 * i] += t.x; sum[4 * i + 1] += t.y; sum[4 * i + 2] += t.z; sum[4 * i + 3] += t.w;
          }
          add_partial(sum, v, pbase + ((j - 7) & 7) * (8 * 128), tagbits);
          WG_WAIT(0);
          pin(acc);
#pragma unroll
          for (int i = 0; i < 56; i++) sum[i] += acc[i];
          uint32_t pk[28];
          pack_tile(pk, sum);
          const uint32_t stg = slots + (100 % NSLOT) * SLOT_BYTES;
          store_tile_t(stg, pk, wi, lane);
          named_bar(2, 128);
          uint4* orow = reinterpret_cast<uint4*>(gout + (size_t)(b * SQ + (t128 >> 3)) * DM + j * 64) + (t128 & 7);
          const uint32_t src = stg + (t128 >> 3) * 128 + (((t128 & 7) ^ ((t128 >> 3) & 7)) << 4);
#pragma unroll
          for (int i = 0; i < 7; i++) {
            uint4 t;
            asm volatile("ld.shared.v4.u32 {%0, %1, %2, %3}, [%4];" : "=r"(t.x), "=r"(t.y), "=r"(t.z), "=r"(t.w) : "r"(src + i * 2048) : "memory");
            orow[(size_t)i * 16 * (DM / 8)] = t;
          }
          if (j == 0 && t128 == 0) atomicAdd(g_epoch + b, 1u);
        } else {
          WG_WAIT(0);
          TSTAMP(7 + (s >> 1) * 2);
          pin(acc);
          if (FILL_O0 + s * 4 + 3 < NFILL - NSLOT) release_both(FILL_O0 + s * 4 + 3);
          const float tagf = __uint_as_float(tagbits);
          if (s < 7) {
            uint4* dst = g_part + (size_t)((b * 8 + o_tile_of_step(j, s)) * 8 + j) * (8 * 128) + t128;
#pragma unroll
            for (int i = 0; i < 8; i++) store_chunk(dst + i * 128, acc + 7 * i, tagf);
          } else {
            uint4* dst = g_part8 + (size_t)(((b * 8 + 2 * wi) * 8 + j) * 4) * 32 + lane;
#pragma unroll
            for (int h = 0; h < 2; h++) {
              float e[28];
#pragma unroll
              for (int i = 0; i < 28; i++) e[i] = acc[4 * (i >> 1) + 2 * h + (i & 1)];
#pragma unroll
              for (int c = 0; c < 4; c++) store_chunk(dst + (h * 8 * 4 + c) * 32, e + 7 * c, tagf);
            }
          }
        }
      }
      if (wg == 1) {
        const uint4* s8 = g_part8 + (size_t)(((b * 8 + j) * 8) * 4 + wi) * 32 + lane;
        add_partial(sum, v, pbase + ((j - 5) & 7) * (8 * 128), tagbits);
        add_partial(sum, v2, pbase + ((j - 6) & 7) * (8 * 128), tagbits);
        named_bar(3, 128);
#pragma unroll
        for (int i = 0; i < 14; i++)
          asm volatile("st.shared.v4.f32 [%0], {%1, %2, %3, %4};" ::"r"(xch + i * 2048), "f"(sum[4 * i]), "f"(sum[4 * i + 1]), "f"(sum[4 * i + 2]), "f"(sum[4 * i + 3]) : "memory");
        named_arrive(1, 256);
        load_chunks(v, s8, 4 * 32);
        check_chunks(v, s8, 4 * 32, tagbits);
        float r[7];
#pragma unroll
        for (int i = 0; i < 7; i++) r[i] = 0.f;
#pragma unroll
        for (int d = 0; d < 8; d++) add_chunk(r, v[d]);
        const int odd = wi & 1;
        __nv_bfloat16* dst = gout + (size_t)(b * SQ + 4 * (7 * wi - odd) + 2 * (lane & 3)) * DM + 512 + 8 * j + (lane >> 2);
        __nv_bfloat16* dA = dst + odd * DM;
        __nv_bfloat16* dB = dst + (1 + 7 * odd) * DM;
#pragma unroll
        for (int i = 0; i < 7; i++) ((i & 1) ? dB : dA)[(i >> 1) * 8 * DM] = __float2bfloat16(r[i]);
      }
    }
    TSTAMP(6);
  }
}

typedef CUresult (*EncodeFn)(CUtensorMap*, CUtensorMapDataType, cuuint32_t, void*, const cuuint64_t*, const cuuint64_t*,
                             const cuuint32_t*, const cuuint32_t*, CUtensorMapInterleave, CUtensorMapSwizzle,
                             CUtensorMapL2promotion, CUtensorMapFloatOOBfill);

void make_map(EncodeFn enc, CUtensorMap* m, const void* ptr, int rank, const cuuint64_t* dims, const cuuint64_t* strides,
              const cuuint32_t* box) {
  cuuint32_t es[3] = {1, 1, 1};
  enc(m, CU_TENSOR_MAP_DATA_TYPE_BFLOAT16, rank, const_cast<void*>(ptr), dims, strides, box, es, CU_TENSOR_MAP_INTERLEAVE_NONE,
      CU_TENSOR_MAP_SWIZZLE_128B, CU_TENSOR_MAP_L2_PROMOTION_L2_256B, CU_TENSOR_MAP_FLOAT_OOB_FILL_NONE);
}

}

extern "C" void kernel_launch(void* const* d_in, const int* in_sizes, int n_in, void* d_out, int out_size) {
  (void)in_sizes; (void)n_in; (void)out_size;
  static EncodeFn enc = nullptr;
  if (!enc) {
    void* fn = nullptr;
    cudaDriverEntryPointQueryResult qr;
    cudaGetDriverEntryPoint("cuTensorMapEncodeTiled", &fn, cudaEnableDefault, &qr);
    enc = (EncodeFn)fn;
    cudaFuncSetAttribute(gqa_fused_kernel, cudaFuncAttributeMaxDynamicSharedMemorySize, SMEM_BYTES);
  }
  CUtensorMap tx, tk, tv, twq, two;
  {
    cuuint64_t d[2] = {DM, B_ * SQ}, s[1] = {DM * 2}; cuuint32_t bx[2] = {64, SQ};
    make_map(enc, &tx, d_in[0], 2, d, s, bx);
  }
  {
    cuuint64_t d[3] = {64, (cuuint64_t)B_ * HKV * SK, 2}, s[2] = {DH * 2, 128}; cuuint32_t bx[3] = {64, 64, 2};
    make_map(enc, &tk, d_in[1], 3, d, s, bx);
    make_map(enc, &tv, d_in[2], 3, d, s, bx);
  }
  {
    cuuint64_t d[2] = {HQ * DH, DM}, s[1] = {HQ * DH * 2}; cuuint32_t bx[2] = {64, 64};
    make_map(enc, &twq, d_in[3], 2, d, s, bx);
  }
  {
    cuuint64_t d[2] = {DM, HQ * DH}, s[1] = {DM * 2}; cuuint32_t bx[2] = {64, 64};
    make_map(enc, &two, d_in[4], 2, d, s, bx);
  }
  gqa_fused_kernel<<<128, NTHREADS, SMEM_BYTES>>>(tx, tk, tv, twq, two, (const uint8_t*)d_in[0], (const uint8_t*)d_in[1], (const uint8_t*)d_in[2],
                                                   (const uint8_t*)d_in[3], (const uint8_t*)d_in[4], (__nv_bfloat16*)d_out);
}
```

```cpp
#include <cuda_runtime.h>
#include <cuda_bf16.h>
#include <cuda.h>
#include <stdint.h>

namespace {

constexpr int B_ = 16, SQ = 112, DM = 576, HQ = 32, HKV = 16, SK = 512, DH = 128;
constexpr int NSLOT = 6;
constexpr int SLOT_BYTES = 16384;
constexpr int BLK = 112 * 128;
constexpr int NFILL_Q = 36, NFILL_KV = 32, NFILL_O = 36;
constexpr int FILL_KV0 = NFILL_Q, FILL_O0 = NFILL_Q + NFILL_KV, NFILL = FILL_O0 + NFILL_O;
constexpr int OFF_SLOTS = 8 * BLK;
constexpr int OFF_STAGE = OFF_SLOTS + NSLOT * SLOT_BYTES;
constexpr int OFF_BARS = OFF_STAGE + BLK;
constexpr int NBARS = 2 * NFILL + 9 + 1;
constexpr int SMEM_BYTES = OFF_BARS + NBARS * 8 + 64;
constexpr int NTHREADS = 384;
#define PF_DIST 10
#define PF_Q0 8
#define PF_QS 6
#define PF_LAG 2
#define PF_SPAN 26
constexpr uint32_t SPIN_LIMIT = 1u << 22;

__device__ uint4 g_part[B_ * 8 * 8 * 8 * 128];
__device__ uint4 g_part8[B_ * 8 * 8 * 4 * 32];
__device__ uint32_t g_epoch[B_];

#define TSTAMP(i) do {} while (0)

__device__ __forceinline__ uint32_t smem_u32(const void* p) { return (uint32_t)__cvta_generic_to_shared(p); }
__device__ __forceinline__ void mbar_init(uint32_t bar, uint32_t cnt) { asm volatile("mbarrier.init.shared::cta.b64 [%0], %1;" ::"r"(bar), "r"(cnt) : "memory"); }
__device__ __forceinline__ void mbar_expect_tx(uint32_t bar, uint32_t bytes) { asm volatile("mbarrier.arrive.expect_tx.shared::cta.b64 _, [%0], %1;" ::"r"(bar), "r"(bytes) : "memory"); }
__device__ __forceinline__ void mbar_arrive_pred(uint32_t bar, bool p) { asm volatile("{\n.reg .pred p;\nsetp.ne.b32 p, %1, 0;\n@p mbarrier.arrive.shared::cta.b64 _, [%0];\n}\n" ::"r"(bar), "r"((int)p) : "memory"); }
__device__ __forceinline__ void mbar_arrive_remote_pred(uint32_t rbar, bool p) { asm volatile("{\n.reg .pred p;\nsetp.ne.b32 p, %1, 0;\n@p mbarrier.arrive.shared::cluster.b64 _, [%0];\n}\n" ::"r"(rbar), "r"((int)p) : "memory"); }
__device__ __forceinline__ void mbar_wait_sleep(uint32_t bar) {
  uint32_t done, it = 0;
  do {
    asm volatile("{\n.reg .pred p;\nmbarrier.try_wait.parity.shared::cta.b64 p, [%1], 0, %2;\nselp.u32 %0, 1, 0, p;\n}\n" : "=r"(done) : "r"(bar), "r"(100000u) : "memory");
    if (++it > 4096) break;
  } while (!done);
}
__device__ __forceinline__ void mbar_wait(uint32_t bar) {
  uint32_t done, it = 0;
  do {
    asm volatile("{\n.reg .pred p;\nmbarrier.try_wait.parity.shared::cta.b64 p, [%1], 0;\nselp.u32 %0, 1, 0, p;\n}\n" : "=r"(done) : "r"(bar) : "memory");
    if (++it > SPIN_LIMIT) break;
  } while (!done);
}
__device__ __forceinline__ uint32_t mapa(uint32_t addr, uint32_t cta) { uint32_t r; asm volatile("mapa.shared::cluster.u32 %0, %1, %2;" : "=r"(r) : "r"(addr), "r"(cta)); return r; }
__device__ __forceinline__ void tma_2d(uint32_t dst, const CUtensorMap* m, int c0, int c1, uint32_t bar) {
  asm volatile("cp.async.bulk.tensor.2d.shared::cluster.global.mbarrier::complete_tx::bytes [%0], [%1, {%3, %4}], [%2];" ::"r"(dst), "l"(m), "r"(bar), "r"(c0), "r"(c1) : "memory");
}
__device__ __forceinline__ void tma_2d_mc(uint32_t dst, const CUtensorMap* m, int c0, int c1, uint32_t bar) {
  asm volatile("cp.async.bulk.tensor.2d.shared::cluster.global.mbarrier::complete_tx::bytes.multicast::cluster [%0], [%1, {%3, %4}], [%2], %5;" ::"r"(dst), "l"(m), "r"(bar), "r"(c0), "r"(c1), "h"((uint16_t)3) : "memory");
}
__device__ __forceinline__ void tma_3d(uint32_t dst, const CUtensorMap* m, int c0, int c1, int c2, uint32_t bar) {
  asm volatile("cp.async.bulk.tensor.3d.shared::cluster.global.mbarrier::complete_tx::bytes [%0], [%1, {%3, %4, %5}], [%2];" ::"r"(dst), "l"(m), "r"(bar), "r"(c0), "r"(c1), "r"(c2) : "memory");
}
__device__ __forceinline__ uint4 ld_relaxed_b128(const uint4* p) {
  uint4 v;
  asm volatile("{\n.reg .b64 l, h;\n.reg .b128 t;\nld.relaxed.gpu.global.b128 t, [%4];\nmov.b128 {l, h}, t;\n"
               "mov.b64 {%0, %1}, l;\nmov.b64 {%2, %3}, h;\n}\n" : "=r"(v.x), "=r"(v.y), "=r"(v.z), "=r"(v.w) : "l"(p) : "memory");
  return v;
}
__device__ __forceinline__ void l2_prefetch(const void* p, uint32_t bytes) { asm volatile("cp.async.bulk.prefetch.L2.global [%0], %1;" ::"l"(p), "r"(bytes) : "memory"); }
__device__ __forceinline__ void prefetch_line(const void* p) { asm volatile("prefetch.global.L2 [%0];" ::"l"(p)); }
__device__ __forceinline__ void prefetch_tmap(const CUtensorMap* m) { asm volatile("prefetch.tensormap [%0];" ::"l"(m) : "memory"); }
__device__ __forceinline__ bool elect_one() { uint32_t p; asm volatile("{\n.reg .pred p;\nelect.sync _|p, 0xffffffff;\nselp.u32 %0, 1, 0, p;\n}\n" : "=r"(p)); return p != 0; }
__device__ __forceinline__ void named_bar(int id, int n) { asm volatile("bar.sync %0, %1;" ::"r"(id), "r"(n) : "memory"); }
__device__ __forceinline__ void named_arrive(int id, int n) { asm volatile("bar.arrive %0, %1;" ::"r"(id), "r"(n) : "memory"); }
__device__ __forceinline__ void fence_async_smem() { asm volatile("fence.proxy.async.shared::cta;" ::: "memory"); }
#define WG_FENCE() asm volatile("wgmma.fence.sync.aligned;" ::: "memory")
#define WG_COMMIT() asm volatile("wgmma.commit_group.sync.aligned;" ::: "memory")
#define WG_WAIT(n) asm volatile("wgmma.wait_group.sync.aligned %0;" ::"n"(n) : "memory")
template <int N> __device__ __forceinline__ void pin(float (&d)[N]) {
#pragma unroll
  for (int i = 0; i < N; i++) asm volatile("" : "+f"(d[i])::"memory");
}
__device__ __forceinline__ uint64_t mkdesc(uint32_t lo) { return ((uint64_t)(64u | (1u << 30)) << 32) | lo; }
__device__ __forceinline__ uint32_t pack_bf16(float lo, float hi) { uint32_t r; asm("cvt.rn.bf16x2.f32 %0, %1, %2;" : "=r"(r) : "f"(hi), "f"(lo)); return r; }
__device__ __forceinline__ float ex2(float x) { float r; asm("ex2.approx.ftz.f32 %0, %1;" : "=f"(r) : "f"(x)); return r; }
__device__ __forceinline__ float rcp_fast(float x) { float r; asm("rcp.approx.ftz.f32 %0, %1;" : "=f"(r) : "f"(x)); return r; }
__device__ __forceinline__ void stsm_x4(uint32_t addr, uint32_t r0, uint32_t r1, uint32_t r2, uint32_t r3) {
  asm volatile("stmatrix.sync.aligned.m8n8.x4.shared.b16 [%0], {%1, %2, %3, %4};" ::"r"(addr), "r"(r0), "r"(r1), "r"(r2), "r"(r3) : "memory");
}
__device__ __forceinline__ void stsm_x4_t(uint32_t addr, uint32_t r0, uint32_t r1, uint32_t r2, uint32_t r3) {
  asm volatile("stmatrix.sync.aligned.m8n8.x4.trans.shared.b16 [%0], {%1, %2, %3, %4};" ::"r"(addr), "r"(r0), "r"(r1), "r"(r2), "r"(r3) : "memory");
}

__device__ __forceinline__ void wgmma_n112_ta(float (&d)[56], uint64_t da, uint64_t db, int sc) {
  asm volatile("{\n.reg .pred p;\nsetp.ne.b32 p, %58, 0;\n"
    "wgmma.mma_async.sync.aligned.m64n112k16.f32.bf16.bf16 "
    "{%0, %1, %2, %3, %4, %5, %6, %7, %8, %9, %10, %11, %12, %13, %14, %15, %16, %17, %18, %19, %20, %21, %22, %23, %24, %25, %26, %27, %28, %29, %30, %31, %32, %33, %34, %35, %36, %37, %38, %39, %40, %41, %42, %43, %44, %45, %46, %47, %48, %49, %50, %51, %52, %53, %54, %55}, "
    "%56, %57, p, 1, 1, 1, 0;\n}\n"
    : "+f"(d[0]), "+f"(d[1]), "+f"(d[2]), "+f"(d[3]), "+f"(d[4]), "+f"(d[5]), "+f"(d[6]), "+f"(d[7]), "+f"(d[8]), "+f"(d[9]), "+f"(d[10]), "+f"(d[11]), "+f"(d[12]), "+f"(d[13]), "+f"(d[14]), "+f"(d[15]), "+f"(d[16]), "+f"(d[17]), "+f"(d[18]), "+f"(d[19]), "+f"(d[20]), "+f"(d[21]), "+f"(d[22]), "+f"(d[23]), "+f"(d[24]), "+f"(d[25]), "+f"(d[26]), "+f"(d[27]), "+f"(d[28]), "+f"(d[29]), "+f"(d[30]), "+f"(d[31]), "+f"(d[32]), "+f"(d[33]), "+f"(d[34]), "+f"(d[35]), "+f"(d[36]), "+f"(d[37]), "+f"(d[38]), "+f"(d[39]), "+f"(d[40]), "+f"(d[41]), "+f"(d[42]), "+f"(d[43]), "+f"(d[44]), "+f"(d[45]), "+f"(d[46]), "+f"(d[47]), "+f"(d[48]), "+f"(d[49]), "+f"(d[50]), "+f"(d[51]), "+f"(d[52]), "+f"(d[53]), "+f"(d[54]), "+f"(d[55])
    : "l"(da), "l"(db), "r"(sc));
}

__device__ __forceinline__ void wgmma_n64_ss(float (&d)[32], uint64_t da, uint64_t db, int sc) {
  asm volatile("{\n.reg .pred p;\nsetp.ne.b32 p, %34, 0;\n"
    "wgmma.mma_async.sync.aligned.m64n64k16.f32.bf16.bf16 "
    "{%0, %1, %2, %3, %4, %5, %6, %7, %8, %9, %10, %11, %12, %13, %14, %15, %16, %17, %18, %19, %20, %21, %22, %23, %24, %25, %26, %27, %28, %29, %30, %31}, "
    "%32, %33, p, 1, 1, 0, 0;\n}\n"
    : "+f"(d[0]), "+f"(d[1]), "+f"(d[2]), "+f"(d[3]), "+f"(d[4]), "+f"(d[5]), "+f"(d[6]), "+f"(d[7]), "+f"(d[8]), "+f"(d[9]), "+f"(d[10]), "+f"(d[11]), "+f"(d[12]), "+f"(d[13]), "+f"(d[14]), "+f"(d[15]), "+f"(d[16]), "+f"(d[17]), "+f"(d[18]), "+f"(d[19]), "+f"(d[20]), "+f"(d[21]), "+f"(d[22]), "+f"(d[23]), "+f"(d[24]), "+f"(d[25]), "+f"(d[26]), "+f"(d[27]), "+f"(d[28]), "+f"(d[29]), "+f"(d[30]), "+f"(d[31])
    : "l"(da), "l"(db), "r"(sc));
}

__device__ __forceinline__ void wgmma_n128_rs(float (&d)[64], uint32_t a0, uint32_t a1, uint32_t a2, uint32_t a3, uint64_t db, int sc) {
  asm volatile("{\n.reg .pred p;\nsetp.ne.b32 p, %69, 0;\n"
    "wgmma.mma_async.sync.aligned.m64n128k16.f32.bf16.bf16 "
    "{%0, %1, %2, %3, %4, %5, %6, %7, %8, %9, %10, %11, %12, %13, %14, %15, %16, %17, %18, %19, %20, %21, %22, %23, %24, %25, %26, %27, %28, %29, %30, %31, %32, %33, %34, %35, %36, %37, %38, %39, %40, %41, %42, %43, %44, %45, %46, %47, %48, %49, %50, %51, %52, %53, %54, %55, %56, %57, %58, %59, %60, %61, %62, %63}, "
    "{%64, %65, %66, %67}, %68, p, 1, 1, 1;\n}\n"
    : "+f"(d[0]), "+f"(d[1]), "+f"(d[2]), "+f"(d[3]), "+f"(d[4]), "+f"(d[5]), "+f"(d[6]), "+f"(d[7]), "+f"(d[8]), "+f"(d[9]), "+f"(d[10]), "+f"(d[11]), "+f"(d[12]), "+f"(d[13]), "+f"(d[14]), "+f"(d[15]), "+f"(d[16]), "+f"(d[17]), "+f"(d[18]), "+f"(d[19]), "+f"(d[20]), "+f"(d[21]), "+f"(d[22]), "+f"(d[23]), "+f"(d[24]), "+f"(d[25]), "+f"(d[26]), "+f"(d[27]), "+f"(d[28]), "+f"(d[29]), "+f"(d[30]), "+f"(d[31]), "+f"(d[32]), "+f"(d[33]), "+f"(d[34]), "+f"(d[35]), "+f"(d[36]), "+f"(d[37]), "+f"(d[38]), "+f"(d[39]), "+f"(d[40]), "+f"(d[41]), "+f"(d[42]), "+f"(d[43]), "+f"(d[44]), "+f"(d[45]), "+f"(d[46]), "+f"(d[47]), "+f"(d[48]), "+f"(d[49]), "+f"(d[50]), "+f"(d[51]), "+f"(d[52]), "+f"(d[53]), "+f"(d[54]), "+f"(d[55]), "+f"(d[56]), "+f"(d[57]), "+f"(d[58]), "+f"(d[59]), "+f"(d[60]), "+f"(d[61]), "+f"(d[62]), "+f"(d[63])
    : "r"(a0), "r"(a1), "r"(a2), "r"(a3), "l"(db), "r"(sc));
}

template <int I0 = 0, int I1 = 7>
__device__ __forceinline__ void store_tile_t(uint32_t blk, const uint32_t (&pk)[28], int wi, int lane) {
  const int mi = lane >> 3, r = lane & 7;
  const uint32_t base = blk + (uint32_t)(((mi >> 1) * 8 + r) * 128 + (((2 * wi + (mi & 1)) ^ r) << 4));
#pragma unroll
  for (int i = I0; i < I1; i++) stsm_x4_t(base + i * 2048, pk[4 * i], pk[4 * i + 1], pk[4 * i + 2], pk[4 * i + 3]);
}
__device__ __forceinline__ void pack_tile(uint32_t (&pk)[28], const float (&a)[56]) {
#pragma unroll
  for (int i = 0; i < 28; i++) pk[i] = pack_bf16(a[2 * i], a[2 * i + 1]);
}

constexpr float SCALE_LOG2E = 0.08838834764831845f * 1.4426950408889634f;
__device__ __forceinline__ void pack_tile_scaled(uint32_t (&pk)[28], const float (&a)[56]) {
#pragma unroll
  for (int i = 0; i < 28; i++) pk[i] = pack_bf16(a[2 * i] * SCALE_LOG2E, a[2 * i + 1] * SCALE_LOG2E);
}

struct RowStat { float m0, m1, l0, l1; };

__device__ __forceinline__ void finish_rows(RowStat& st) {
  float l0 = st.l0, l1 = st.l1;
  l0 += __shfl_xor_sync(0xffffffffu, l0, 1); l1 += __shfl_xor_sync(0xffffffffu, l1, 1);
  l0 += __shfl_xor_sync(0xffffffffu, l0, 2); l1 += __shfl_xor_sync(0xffffffffu, l1, 2);
  st.l0 = rcp_fast(l0); st.l1 = rcp_fast(l1);
}
__device__ __forceinline__ void store_o_tile(uint32_t blk0, int row0, float (&O)[64], const RowStat& st) {
  int tid_;
  asm volatile("mov.u32 %0, %%tid.x;" : "=r"(tid_));
  const int lane = tid_ & 31, wi = (tid_ >> 5) & 3;
  const float i0 = st.l0, i1 = st.l1;
  const int mi = lane >> 3, r = lane & 7;
  const uint32_t base = blk0 + (uint32_t)((row0 + 16 * wi + (mi & 1) * 8 + r) * 128);
#pragma unroll
  for (int i = 0; i < 16; i += 2) {
    const int cg = (i & 7) + (mi >> 1);
    const uint32_t addr = base + (uint32_t)((i >> 3) * BLK) + (uint32_t)((cg ^ r) << 4);
    const uint32_t w0 = pack_bf16(O[4 * i] * i0, O[4 * i + 1] * i0), w1 = pack_bf16(O[4 * i + 2] * i1, O[4 * i + 3] * i1);
    const uint32_t w2 = pack_bf16(O[4 * i + 4] * i0, O[4 * i + 5] * i0), w3 = pack_bf16(O[4 * i + 6] * i1, O[4 * i + 7] * i1);
    stsm_x4(addr, w0, w1, w2, w3);
  }
}

constexpr float SUM_HI = 16777216.0f, SUM_HI_LOG2 = 24.0f, SUM_LO = 1.0f / 16777216.0f;
__device__ __forceinline__ void sub_ref(float (&S)[32], const RowStat& st) {
#pragma unroll
  for (int i = 0; i < 8; i++) { S[4 * i] -= st.m0; S[4 * i + 1] -= st.m0; S[4 * i + 2] -= st.m1; S[4 * i + 3] -= st.m1; }
}
__device__ __forceinline__ void update_ref(float (&T)[32], float (&O)[64], RowStat& st, bool first) {
  float a0 = fmaxf(T[0], T[1]), a1 = fmaxf(T[2], T[3]), b0 = fmaxf(T[4], T[5]), b1 = fmaxf(T[6], T[7]);
#pragma unroll
  for (int i = 2; i < 8; i += 2) {
    a0 = fmaxf(a0, fmaxf(T[4 * i], T[4 * i + 1])); a1 = fmaxf(a1, fmaxf(T[4 * i + 2], T[4 * i + 3]));
    b0 = fmaxf(b0, fmaxf(T[4 * i + 4], T[4 * i + 5])); b1 = fmaxf(b1, fmaxf(T[4 * i + 6], T[4 * i + 7]));
  }
  float d0 = fmaxf(a0, b0), d1 = fmaxf(a1, b1);
  d0 = fmaxf(d0, __shfl_xor_sync(0xffffffffu, d0, 1)); d1 = fmaxf(d1, __shfl_xor_sync(0xffffffffu, d1, 1));
  d0 = fmaxf(d0, __shfl_xor_sync(0xffffffffu, d0, 2)); d1 = fmaxf(d1, __shfl_xor_sync(0xffffffffu, d1, 2));
  if (first) {
    st.m0 = d0; st.m1 = d1;
  } else {
    d0 = fmaxf(d0, 0.f); d1 = fmaxf(d1, 0.f);
    const float r0 = ex2(-d0), r1 = ex2(-d1);
    st.m0 += d0; st.m1 += d1; st.l0 *= r0; st.l1 *= r1;
#pragma unroll
    for (int i = 0; i < 16; i++) { O[4 * i] *= r0; O[4 * i + 1] *= r0; O[4 * i + 2] *= r1; O[4 * i + 3] *= r1; }
  }
#pragma unroll
  for (int i = 0; i < 8; i++) { T[4 * i] -= d0; T[4 * i + 1] -= d0; T[4 * i + 2] -= d1; T[4 * i + 3] -= d1; }
}
__device__ __forceinline__ bool softmax_exp(const float (&T)[32], uint32_t (&P)[16], float& l0, float& l1, float lo) {
  const bool ok_last = fmaxf(fmaxf(T[28], T[29]), fmaxf(T[30], T[31])) <= SUM_HI_LOG2;
  bool bad = false;
#pragma unroll
  for (int i = 0; i < 8; i++) {
    if (i == 7) bad = __any_sync(0xffffffffu, !(fmaxf(l0, l1) <= SUM_HI && fminf(l0, l1) >= lo && ok_last));
    const float p0 = ex2(T[4 * i]), p1 = ex2(T[4 * i + 1]), p2 = ex2(T[4 * i + 2]), p3 = ex2(T[4 * i + 3]);
    if (i == 0) { l0 = p0; l1 = p2; } else { l0 += p0; l1 += p2; }
    l0 += p1; l1 += p3;
    P[2 * i] = pack_bf16(p0, p1); P[2 * i + 1] = pack_bf16(p2, p3);
  }
  return bad;
}
__device__ __forceinline__ void softmax_tile(float (&T)[32], float (&O)[64], uint32_t (&P)[16], RowStat& st, bool& sub, bool first) {
  float l0, l1;
  if (__builtin_expect(softmax_exp(T, P, l0, l1, first ? SUM_LO : 0.f), 0)) {
    update_ref(T, O, st, first);
    sub = true;
    softmax_exp(T, P, l0, l1, 0.f);
  }
  st.l0 += l0; st.l1 += l1;
}

__device__ __forceinline__ void issue_s(float (&S)[32], uint32_t q16, uint32_t k16) {
  const uint64_t dq = mkdesc(q16), dk = mkdesc(k16);
#pragma unroll
  for (int kk = 0; kk < 8; kk++)
    wgmma_n64_ss(S, dq + ((kk >> 2) * (BLK / 16) + (kk & 3) * 2), dk + ((kk >> 2) * 512 + (kk & 3) * 2), kk != 0);
}
__device__ __forceinline__ void issue_pv(float (&O)[64], const uint32_t (&P)[16], uint32_t v16, int acc) {
  const uint64_t dv = mkdesc(v16 + (512u << 16));
#pragma unroll
  for (int kk = 0; kk < 4; kk++)
    wgmma_n128_rs(O, P[4 * kk], P[4 * kk + 1], P[4 * kk + 2], P[4 * kk + 3], dv + kk * 128, kk ? 1 : acc);
}

__device__ __forceinline__ int o_tile_of_step(int j, int s) { return s == 7 ? 8 : ((j + 1 + s - (s == 8)) & 7); }
__device__ __forceinline__ int o_quarter(int kq) { return ((kq & 1) << 1) | (kq >> 1); }

__device__ __forceinline__ void store_chunk(uint4* p, const float* a, float tagf) {
  asm volatile("st.relaxed.gpu.global.v4.b32 [%0], {%1, %2, %3, %4};" ::"l"(p), "r"(pack_bf16(a[0], a[1])),
               "r"(pack_bf16(a[2], a[3])), "r"(pack_bf16(a[4], a[5])), "r"(pack_bf16(a[6], tagf)) : "memory");
}
__device__ __forceinline__ void add_chunk(float* a, const uint4& v) {
  a[0] += __uint_as_float(v.x << 16); a[1] += __uint_as_float(v.x & 0xffff0000u);
  a[2] += __uint_as_float(v.y << 16); a[3] += __uint_as_float(v.y & 0xffff0000u);
  a[4] += __uint_as_float(v.z << 16); a[5] += __uint_as_float(v.z & 0xffff0000u);
  a[6] += __uint_as_float(v.w << 16);
}
__device__ __forceinline__ void load_chunks(uint4 (&v)[8], const uint4* p, int stride) {
#pragma unroll
  for (int i = 0; i < 8; i++) v[i] = ld_relaxed_b128(p + i * stride);
}
__device__ __forceinline__ void check_chunks(uint4 (&v)[8], const uint4* p, int stride, uint32_t tagbits) {
  uint32_t it = 0;
  for (;;) {
    uint32_t bad = 0;
#pragma unroll
    for (int i = 0; i < 8; i++) bad |= v[i].w ^ tagbits;
    if (!__any_sync(0xffffffffu, bad > 0xffffu) || ++it > SPIN_LIMIT) break;
    load_chunks(v, p, stride);
  }
}
__device__ __forceinline__ void add_partial(float (&a)[56], uint4 (&v)[8], const uint4* p, uint32_t tagbits) {
  check_chunks(v, p, 128, tagbits);
#pragma unroll
  for (int i = 0; i < 8; i++) add_chunk(a + 7 * i, v[i]);
}

__host__ __device__ constexpr uint32_t bar_count(int i) {
  return i >= 2 * NFILL ? 1
       : i >= NFILL ? ((i - NFILL >= FILL_O0 - NSLOT && i - NFILL < FILL_O0) ? 16 : 8)
       : (i > FILL_KV0 && i < FILL_O0 - 1) ? 2 : 1;
}
template <int W> __device__ __forceinline__ void init_barriers(uint32_t base, int w) {
  constexpr int NW = NTHREADS / 32 - 1, PER = (NBARS + NW - 1) / NW;
  if (w == W) {
#pragma unroll
    for (int i = W * PER; i < (W + 1) * PER && i < NBARS; i++)
      if (i > 1 && i != 2 * NFILL && i != 2 * NFILL + 1) mbar_init(base + i * 8, bar_count(i));
  } else if constexpr (W + 1 < NW) {
    init_barriers<W + 1>(base, w);
  }
}

__global__ void __cluster_dims__(2, 1, 1) __launch_bounds__(NTHREADS, 1)
gqa_fused_kernel(const __grid_constant__ CUtensorMap tm_x, const __grid_constant__ CUtensorMap tm_k,
                 const __grid_constant__ CUtensorMap tm_v, const __grid_constant__ CUtensorMap tm_wq,
                 const __grid_constant__ CUtensorMap tm_wo, const uint8_t* __restrict__ gx,
                 const uint8_t* __restrict__ gk, const uint8_t* __restrict__ gv, const uint8_t* __restrict__ gwq,
                 const uint8_t* __restrict__ gwo, __nv_bfloat16* __restrict__ gout) {
  extern __shared__ __align__(1024) uint8_t smem[];
  const uint32_t sb = smem_u32(smem);
  const uint32_t slots = sb + OFF_SLOTS;
  const uint32_t bar_full = sb + OFF_BARS, bar_empty = bar_full + NFILL * 8, bar_x = bar_empty + NFILL * 8, bar_tag = bar_x + 9 * 8,
                 s_tag = bar_tag + 8, stage = sb + OFF_STAGE;
  const int tid = threadIdx.x, lane = tid & 31;
  const int wg = __shfl_sync(0xffffffffu, tid >> 7, 0), wi = __shfl_sync(0xffffffffu, (tid >> 5) & 3, 0);
  const uint32_t rank = blockIdx.x & 1;
  const int cl = blockIdx.x >> 1;
  const int j = cl & 7, b = (cl >> 3) * 2 + (int)rank;

  TSTAMP(0);
  if (tid < 32) prefetch_line(gwq + (size_t)(64 + b * 8 + (tid >> 2)) * (HQ * DH * 2) + j * 1024 + (tid & 3) * 128);
  else if (tid < 60) prefetch_line(gx + (size_t)(b * SQ + j * 14 + ((tid - 32) >> 1)) * (DM * 2) + 256 + (tid & 1) * 128);
  if (tid == 256) {
    mbar_init(bar_full, 1); mbar_init(bar_full + 8, 1); mbar_init(bar_x, 1); mbar_init(bar_x + 8, 1);
    asm volatile("fence.mbarrier_init.release.cluster;" ::: "memory");
    fence_async_smem();
    mbar_expect_tx(bar_x, BLK);
    tma_2d(sb, &tm_x, 0, b * SQ, bar_x);
#pragma unroll
    for (int w = 0; w < 2; w++) {
      mbar_expect_tx(bar_full + w * 8, SLOT_BYTES);
      tma_2d(slots + w * SLOT_BYTES, &tm_wq, (4 * j + w) * DH, 0, bar_full + w * 8);
      tma_2d(slots + w * SLOT_BYTES + 8192, &tm_wq, (4 * j + w) * DH + 64, 0, bar_full + w * 8);
    }
    mbar_expect_tx(bar_x + 8, BLK);
    tma_2d(sb + BLK, &tm_x, 64, b * SQ, bar_x + 8);
  } else if (lane == 0) {
    init_barriers<0>(bar_full, wg * 4 + wi - (wg == 2));
    asm volatile("fence.mbarrier_init.release.cluster;" ::: "memory");
    if (tid == 288) { prefetch_tmap(&tm_k); prefetch_tmap(&tm_v); prefetch_tmap(&tm_wo); }
  }
  __syncwarp();
  __syncthreads();
  asm volatile("barrier.cluster.arrive.relaxed.aligned;" ::: "memory");
  __syncwarp();
  asm volatile("barrier.cluster.wait.acquire.aligned;" ::: "memory");

  if (wg == 2) {
    asm volatile("setmaxnreg.dec.sync.aligned.u32 24;");
    if (wi < 2) {
      const uint32_t slot0 = slots + wi * SLOT_BYTES;
      uint32_t dst = slot0, fb = bar_full + wi * 8;
      auto next = [&]() { dst = (dst == slot0 + 4 * SLOT_BYTES) ? slot0 : dst + 2 * SLOT_BYTES; fb += 16; };
      constexpr uint32_t EMPTY_OFF = NFILL * 8 - NSLOT * 8;
      int c0 = (4 * j + wi) * DH + (int)rank * 64;
      next();
#pragma unroll 1
      for (int t = 1; t < 18; t++) {
        const int k = t < 9 ? t : t - 9;
        if (t == 9) c0 += 2 * DH;
        if (t >= 3) mbar_wait_sleep(fb + EMPTY_OFF);
        if (elect_one()) {
          mbar_expect_tx(fb, SLOT_BYTES);
          tma_2d_mc(dst + rank * 8192, &tm_wq, c0, k * 64, fb);
          if (t < 8 && wi == 1) {
            mbar_expect_tx(bar_x + (t + 1) * 8, BLK);
            tma_2d(t < 7 ? sb + (t + 1) * BLK : stage, &tm_x, (t + 1) * 64, b * SQ, bar_x + (t + 1) * 8);
          }
        }
        next();
      }
      fb += 16 * 16;
      dst = slot0 + (FILL_O0 % NSLOT) * SLOT_BYTES;
      const int r0 = j * 512 + wi * 256 + (int)rank * 64;
#pragma unroll 1
      for (int t = 0; t < 18; t++) {
        mbar_wait_sleep(fb + EMPTY_OFF + ((wi && t < 2) ? 8 : 0));
        const int cw = o_tile_of_step(j, t >> 1) * 64;
        if (elect_one()) {
          mbar_expect_tx(fb, SLOT_BYTES);
          tma_2d_mc(dst + rank * 8192, &tm_wo, cw, r0 + (t & 1) * 128, fb);
        }
        next();
      }
    } else if (wi == 2) {
      const size_t kv0 = (size_t)(b * HKV + 2 * j) * SK * DH * 2;
#pragma unroll 1
      for (int c = 0; c < PF_DIST; c++) {
        mbar_wait_sleep(bar_full + (PF_Q0 + (c * PF_QS) / 2) * 8);
        if (elect_one()) l2_prefetch(((c & 1) ? gv : gk) + kv0 + (size_t)(c >> 1) * 16384, 16384);
      }
    } else if (wi == 3) {
      const uint8_t* wq0 = gwq + (size_t)b * (HQ * DH * 2) + j * 1024 + (lane & 3) * 128;
#pragma unroll
      for (int i = 0; i < 3; i++) prefetch_line(wq0 + (size_t)(192 + 16 * (i * 8 + (lane >> 2))) * (HQ * DH * 2));
      if ((lane & 15) < 14) {
        const uint8_t* xr = gx + (size_t)(b * SQ + j * 14 + (lane & 15)) * (DM * 2) + (4 + (lane >> 4)) * 128;
        prefetch_line(xr); prefetch_line(xr + 256);
        if (lane < 16) prefetch_line(xr + 512);
      }
      mbar_wait_sleep(bar_full + 2 * 8);
#pragma unroll
      for (int i = 0; i < 5; i++)
        if (i * 8 + (lane >> 2) < 36) prefetch_line(wq0 + 512 + (size_t)(16 * (i * 8 + (lane >> 2))) * (HQ * DH * 2));
      if (lane == 0) {
        const uint32_t e = *reinterpret_cast<volatile uint32_t*>(g_epoch + b);
        asm volatile("st.shared.u32 [%0], %1;" ::"r"(s_tag), "r"((0x0800u + e % 0x7000u) << 16) : "memory");
        mbar_arrive_pred(bar_tag, true);
      }
      __syncwarp();
      const int row0 = (b * HKV + 2 * j) * SK;
      const size_t kv0 = (size_t)(b * HKV + 2 * j) * SK * DH * 2;
      uint32_t dst = slots;
      int pf = PF_DIST, acc = 0;
#pragma unroll 1
      for (int c = 0; c < 32; c++) {
        if (c < 7 || (c & 1)) mbar_wait_sleep(bar_empty + (FILL_KV0 - NSLOT + c + (c >= 7)) * 8);
        const uint32_t f = bar_full + (FILL_KV0 + c - ((c > 0 && !(c & 1)) ? 1 : 0)) * 8;
        acc += (c >= PF_LAG) ? 32 - PF_DIST : 0;
        const bool dopf = acc >= PF_SPAN && pf < 32;
        if (elect_one()) {
          mbar_expect_tx(f, SLOT_BYTES);
          tma_3d(dst, (c & 1) ? &tm_v : &tm_k, 0, row0 + (c >> 1) * 64, 0, f);
          if (dopf) l2_prefetch(((pf & 1) ? gv : gk) + kv0 + (size_t)(pf >> 1) * 16384, 16384);
          if (c >= 29) l2_prefetch(gwo + (size_t)j * (512 * DM * 2) + (size_t)b * 36864 + (c - 29) * 12288, 12288);
        }
        if (dopf) { pf++; acc -= PF_SPAN; }
        dst = (dst == slots + 5 * SLOT_BYTES) ? slots : dst + SLOT_BYTES;
      }
    }
  } else {
    asm volatile("setmaxnreg.inc.sync.aligned.u32 240;");
    const uint32_t peer_empty = mapa(bar_empty, rank ^ 1);
    const uint32_t dsb = (sb & 0x3FFFF) >> 4, dslots = dsb + OFF_SLOTS / 16;
    constexpr uint32_t BLK16 = BLK / 16, SLOT16 = SLOT_BYTES / 16;
    auto release_both = [&](int n) { mbar_arrive_pred(bar_empty + n * 8, lane == 0); mbar_arrive_remote_pred(peer_empty + n * 8, lane == 0); };
    auto release_kv = [&](int n) {
      mbar_arrive_pred(bar_empty + n * 8, lane == 0);
      mbar_arrive_remote_pred(peer_empty + n * 8, lane == 0 && n >= FILL_O0 - NSLOT);
    };
    TSTAMP(1);
    const uint32_t qblk = sb + (2 * wg) * BLK, dq = dsb + (2 * wg) * BLK16;
    float Sa[32];
    {
      float acc0[56], acc1[56];
      uint32_t q0[28], q1[28];
      if (wg == 1) named_arrive(4, 256);
      auto q_step = [&](int n, int k) {
        const uint64_t da = mkdesc(dslots + (n % NSLOT) * SLOT16), db = mkdesc(dsb + (k < 8 ? k * BLK16 : OFF_STAGE / 16));
        mbar_wait(bar_full + n * 8);
        named_bar(4 + wg, 256);
        WG_FENCE();
#pragma unroll
        for (int kk = 0; kk < 4; kk++) {
          wgmma_n112_ta(acc0, da + kk * 128, db + kk * 2, (k | kk) != 0);
          wgmma_n112_ta(acc1, da + (512 + kk * 128), db + kk * 2, (k | kk) != 0);
        }
        WG_COMMIT();
        named_arrive(4 + (wg ^ 1), 256);
        if (k > 0) { WG_WAIT(1); release_both(n - 2); }
      };
#pragma unroll 1
      for (int k = 0; k < 9; k++) {
        mbar_wait(bar_x + k * 8);
        q_step(k * 2 + wg, k);
      }
      WG_WAIT(0);
      release_both(16 + wg);
      pin(acc0); pin(acc1);
      pack_tile_scaled(q0, acc0); pack_tile_scaled(q1, acc1);
#pragma unroll 1
      for (int k = 0; k < 9; k++) {
        q_step(18 + k * 2 + wg, k);
        if (k == 4 + wg) store_tile_t<0, 4>(qblk, q0, wi, lane);
        if (k == 5 + wg) store_tile_t<4, 7>(qblk, q0, wi, lane);
        if (k == 6 + wg) store_tile_t<0, 4>(qblk + BLK, q1, wi, lane);
        if (k == 7 + wg) store_tile_t<4, 7>(qblk + BLK, q1, wi, lane);
      }
      TSTAMP(2);
      WG_WAIT(0);
      release_both(34 + wg);
      fence_async_smem();
      mbar_wait(bar_full + FILL_KV0 * 8);
      named_bar(4 + wg, 256);
      WG_FENCE();
      issue_s(Sa, dq, dslots + (FILL_KV0 % NSLOT) * SLOT16);
      WG_COMMIT();
      named_arrive(4 + (wg ^ 1), 256);
      pin(acc0); pin(acc1);
      pack_tile_scaled(q0, acc0); pack_tile_scaled(q1, acc1);
      store_tile_t(qblk + 4 * BLK, q0, wi, lane);
      store_tile_t(qblk + 5 * BLK, q1, wi, lane);
    }
    TSTAMP(3);
    {
      float Oa[64], Ob[64], Sb[32];
      uint32_t P[16];
      RowStat sa, sbt;
      WG_WAIT(0);
      fence_async_smem();
      sa.m0 = sa.m1 = sbt.m0 = sbt.m1 = 0.f; sa.l0 = sa.l1 = sbt.l0 = sbt.l1 = 0.f;
      int slot_k = FILL_KV0 % NSLOT;
      bool suba = false, subb = false;
      uint32_t vprev = dslots + slot_k * SLOT16;
#pragma unroll 1
      for (int jj = 0; jj < 16; jj++) {
        const int nk = FILL_KV0 + 2 * jj;
        const uint32_t kcur = dslots + slot_k * SLOT16, vaddr = kcur + SLOT16;
        slot_k = (slot_k == NSLOT - 2) ? 0 : slot_k + 2;
        const uint32_t knext = dslots + slot_k * SLOT16;
        const bool first = (jj & 7) == 0;
        if (jj == 1) TSTAMP(8); if (jj == 8) TSTAMP(10); if (jj == 10) TSTAMP(12); if (jj == 15) TSTAMP(14);
        named_bar(4 + wg, 256);
        WG_FENCE();
        issue_pv(Ob, P, vprev, (jj & 7) != 1);
        WG_COMMIT();
        issue_s(Sb, dq + (jj >= 8 ? 4 * BLK16 : 0) + 512, kcur);
        WG_COMMIT();
        named_arrive(4 + (wg ^ 1), 256);
        if (jj == 8) finish_rows(sa);
        WG_WAIT(1);
        pin(Oa); pin(Sa);
        if (__builtin_expect(jj == 8 || suba, 0)) {
          if (jj == 8) {
            store_o_tile(qblk, 0, Oa, sa);
            sa.m0 = sa.m1 = sa.l0 = sa.l1 = 0.f; suba = false;
          } else {
            sub_ref(Sa, sa);
          }
        }
        softmax_tile(Sa, Oa, P, sa, suba, first);
        mbar_wait(bar_full + (nk + 1) * 8);
        WG_WAIT(0);
        release_kv(nk);
        named_bar(4 + wg, 256);
        WG_FENCE();
        issue_pv(Oa, P, vaddr, !first);
        WG_COMMIT();
        issue_s(Sa, dq + (jj >= 7 ? 4 * BLK16 : 0), knext);
        WG_COMMIT();
        named_arrive(4 + (wg ^ 1), 256);
        if (jj == 8) finish_rows(sbt);
        WG_WAIT(1);
        pin(Ob); pin(Sb);
        if (wi < 3) {
          if (__builtin_expect(jj == 8 || subb, 0)) {
            if (jj == 8) {
              store_o_tile(qblk, 64, Ob, sbt);
              sbt.m0 = sbt.m1 = sbt.l0 = sbt.l1 = 0.f; subb = false;
            } else {
              sub_ref(Sb, sbt);
            }
          }
          softmax_tile(Sb, Ob, P, sbt, subb, first);
        }
        WG_WAIT(0);
        vprev = vaddr;
      }
      if (wg == 0) named_bar(4, 256);
      WG_FENCE();
      issue_pv(Ob, P, vprev, 1); WG_COMMIT();
      pin(Oa);
      finish_rows(sa); finish_rows(sbt);
      store_o_tile(qblk + 4 * BLK, 0, Oa, sa);
      WG_WAIT(0);
      pin(Ob);
      release_kv(FILL_O0 - 1);
      if (wi < 3) store_o_tile(qblk + 4 * BLK, 64, Ob, sbt);
      fence_async_smem();
      TSTAMP(4);
      if (wg == 1) named_arrive(1, 256);
      named_bar(2 + wg, 128);
    }
    TSTAMP(5);
    {
      const int t128 = tid & 127;
      const uint4* pbase = g_part + (size_t)((b * 8 + j) * 8) * (8 * 128) + t128;
      const uint32_t xch = slots + (98 % NSLOT) * SLOT_BYTES + t128 * 16;
      float sum[56];
      uint4 v[8], v2[8];
      uint32_t tagbits = 0;
#pragma unroll
      for (int i = 0; i < 8; i++) v[i] = v2[i] = make_uint4(0, 0, 0, 0);
#pragma unroll
      for (int i = 0; i < 56; i++) sum[i] = 0.f;
#pragma unroll
      for (int si = 0; si < 5; si++) {
        const int s = 2 * si + (wg & 1);
        if (s > 8) break;
        const int ksplit = (si == 0 || si == 4) ? 2 : 4;
        float acc[56];
        if (s == 8) { add_partial(sum, v, pbase + ((j - 4) & 7) * (8 * 128), tagbits); pin(sum); }
        if (s > 0) named_bar(4 + wg, 256);
#pragma unroll
        for (int kh = 0; kh < 2; kh++) {
          if (kh == 1 && s == 0) named_bar(1, 256);
          if (kh == 1 && s == 8) load_chunks(v, pbase + ((j - 7) & 7) * (8 * 128), 128);
#pragma unroll 1
          for (int kq = (kh ? ksplit : 0); kq < (kh ? 4 : ksplit); kq++) {
            const int n = FILL_O0 + s * 4 + kq;
            const uint64_t da = mkdesc(dslots + (n % NSLOT) * SLOT16), db = mkdesc(dsb + (2 * o_quarter(kq)) * BLK16);
            mbar_wait(bar_full + n * 8);
            WG_FENCE();
#pragma unroll
            for (int kk = 0; kk < 8; kk++)
              wgmma_n112_ta(acc, da + kk * 128, db + ((kk >> 2) * BLK16 + (kk & 3) * 2), kk | kq);
            WG_COMMIT();
            if (kq == 3 && s < 8) named_arrive(4 + (wg ^ 1), 256);
            if (kq > 0) { WG_WAIT(1); if (n - 1 < NFILL - NSLOT) release_both(n - 1); }
          }
        }
        if (s < 2) {
          mbar_wait(bar_tag);
          asm volatile("ld.shared.u32 %0, [%1];" : "=r"(tagbits) : "r"(s_tag) : "memory");
        }
        if (s >= 5 && s < 8) add_partial(sum, v, pbase + ((j + 4 - s) & 7) * (8 * 128), tagbits);
        if (s >= 3 && s < 8) load_chunks(v, pbase + ((j + 2 - s) & 7) * (8 * 128), 128);
        if (s == 7) load_chunks(v2, pbase + ((j - 6) & 7) * (8 * 128), 128);
        pin(sum);
        if (s == 8) {
          TSTAMP(15);
          named_bar(1, 256);
#pragma unroll
          for (int i = 0; i < 14; i++) {
            float4 t;
            asm volatile("ld.shared.v4.f32 {%0, %1, %2, %3}, [%4];" : "=f"(t.x), "=f"(t.y), "=f"(t.z), "=f"(t.w) : "r"(xch + i * 2048) : "memory");
            sum[4 * i] += t.x; sum[4 * i + 1] += t.y; sum[4 * i + 2] += t.z; sum[4 * i + 3] += t.w;
          }
          add_partial(sum, v, pbase + ((j - 7) & 7) * (8 * 128), tagbits);
          WG_WAIT(0);
          pin(acc);
#pragma unroll
          for (int i = 0; i < 56; i++) sum[i] += acc[i];
          uint32_t pk[28];
          pack_tile(pk, sum);
          const uint32_t stg = slots + (100 % NSLOT) * SLOT_BYTES;
          store_tile_t(stg, pk, wi, lane);
          named_bar(2, 128);
          uint4* orow = reinterpret_cast<uint4*>(gout + (size_t)(b * SQ + (t128 >> 3)) * DM + j * 64) + (t128 & 7);
          const uint32_t src = stg + (t128 >> 3) * 128 + (((t128 & 7) ^ ((t128 >> 3) & 7)) << 4);
#pragma unroll
          for (int i = 0; i < 7; i++) {
            uint4 t;
            asm volatile("ld.shared.v4.u32 {%0, %1, %2, %3}, [%4];" : "=r"(t.x), "=r"(t.y), "=r"(t.z), "=r"(t.w) : "r"(src + i * 2048) : "memory");
            orow[(size_t)i * 16 * (DM / 8)] = t;
          }
          if (j == 0 && t128 == 0) atomicAdd(g_epoch + b, 1u);
        } else {
          WG_WAIT(0);
          TSTAMP(7 + (s >> 1) * 2);
          pin(acc);
          if (FILL_O0 + s * 4 + 3 < NFILL - NSLOT) release_both(FILL_O0 + s * 4 + 3);
          const float tagf = __uint_as_float(tagbits);
          if (s < 7) {
            uint4* dst = g_part + (size_t)((b * 8 + o_tile_of_step(j, s)) * 8 + j) * (8 * 128) + t128;
#pragma unroll
            for (int i = 0; i < 8; i++) store_chunk(dst + i * 128, acc + 7 * i, tagf);
          } else {
            uint4* dst = g_part8 + (size_t)(((b * 8 + 2 * wi) * 8 + j) * 4) * 32 + lane;
#pragma unroll
            for (int h = 0; h < 2; h++) {
              float e[28];
#pragma unroll
              for (int i = 0; i < 28; i++) e[i] = acc[4 * (i >> 1) + 2 * h + (i & 1)];
#pragma unroll
              for (int c = 0; c < 4; c++) store_chunk(dst + (h * 8 * 4 + c) * 32, e + 7 * c, tagf);
            }
          }
        }
      }
      if (wg == 1) {
        const uint4* s8 = g_part8 + (size_t)(((b * 8 + j) * 8) * 4 + wi) * 32 + lane;
        add_partial(sum, v, pbase + ((j - 5) & 7) * (8 * 128), tagbits);
        add_partial(sum, v2, pbase + ((j - 6) & 7) * (8 * 128), tagbits);
        named_bar(3, 128);
#pragma unroll
        for (int i = 0; i < 14; i++)
          asm volatile("st.shared.v4.f32 [%0], {%1, %2, %3, %4};" ::"r"(xch + i * 2048), "f"(sum[4 * i]), "f"(sum[4 * i + 1]), "f"(sum[4 * i + 2]), "f"(sum[4 * i + 3]) : "memory");
        named_arrive(1, 256);
        load_chunks(v, s8, 4 * 32);
        check_chunks(v, s8, 4 * 32, tagbits);
        float r[7];
#pragma unroll
        for (int i = 0; i < 7; i++) r[i] = 0.f;
#pragma unroll
        for (int d = 0; d < 8; d++) add_chunk(r, v[d]);
        const int odd = wi & 1;
        __nv_bfloat16* dst = gout + (size_t)(b * SQ + 4 * (7 * wi - odd) + 2 * (lane & 3)) * DM + 512 + 8 * j + (lane >> 2);
        __nv_bfloat16* dA = dst + odd * DM;
        __nv_bfloat16* dB = dst + (1 + 7 * odd) * DM;
#pragma unroll
        for (int i = 0; i < 7; i++) ((i & 1) ? dB : dA)[(i >> 1) * 8 * DM] = __float2bfloat16(r[i]);
      }
    }
    TSTAMP(6);
  }
}

typedef CUresult (*EncodeFn)(CUtensorMap*, CUtensorMapDataType, cuuint32_t, void*, const cuuint64_t*, const cuuint64_t*,
                             const cuuint32_t*, const cuuint32_t*, CUtensorMapInterleave, CUtensorMapSwizzle,
                             CUtensorMapL2promotion, CUtensorMapFloatOOBfill);

void make_map(EncodeFn enc, CUtensorMap* m, const void* ptr, int rank, const cuuint64_t* dims, const cuuint64_t* strides,
              const cuuint32_t* box) {
  cuuint32_t es[3] = {1, 1, 1};
  enc(m, CU_TENSOR_MAP_DATA_TYPE_BFLOAT16, rank, const_cast<void*>(ptr), dims, strides, box, es, CU_TENSOR_MAP_INTERLEAVE_NONE,
      CU_TENSOR_MAP_SWIZZLE_128B, CU_TENSOR_MAP_L2_PROMOTION_L2_128B, CU_TENSOR_MAP_FLOAT_OOB_FILL_NONE);
}

}

extern "C" void kernel_launch(void* const* d_in, const int* in_sizes, int n_in, void* d_out, int out_size) {
  (void)in_sizes; (void)n_in; (void)out_size;
  static EncodeFn enc = nullptr;
  if (!enc) {
    void* fn = nullptr;
    cudaDriverEntryPointQueryResult qr;
    cudaGetDriverEntryPoint("cuTensorMapEncodeTiled", &fn, cudaEnableDefault, &qr);
    enc = (EncodeFn)fn;
    cudaFuncSetAttribute(gqa_fused_kernel, cudaFuncAttributeMaxDynamicSharedMemorySize, SMEM_BYTES);
  }
  CUtensorMap tx, tk, tv, twq, two;
  {
    cuuint64_t d[2] = {DM, B_ * SQ}, s[1] = {DM * 2}; cuuint32_t bx[2] = {64, SQ};
    make_map(enc, &tx, d_in[0], 2, d, s, bx);
  }
  {
    cuuint64_t d[3] = {64, (cuuint64_t)B_ * HKV * SK, 2}, s[2] = {DH * 2, 128}; cuuint32_t bx[3] = {64, 64, 2};
    make_map(enc, &tk, d_in[1], 3, d, s, bx);
    make_map(enc, &tv, d_in[2], 3, d, s, bx);
  }
  {
    cuuint64_t d[2] = {HQ * DH, DM}, s[1] = {HQ * DH * 2}; cuuint32_t bx[2] = {64, 64};
    make_map(enc, &twq, d_in[3], 2, d, s, bx);
  }
  {
    cuuint64_t d[2] = {DM, HQ * DH}, s[1] = {DM * 2}; cuuint32_t bx[2] = {64, 64};
    make_map(enc, &two, d_in[4], 2, d, s, bx);
  }
  gqa_fused_kernel<<<128, NTHREADS, SMEM_BYTES>>>(tx, tk, tv, twq, two, (const uint8_t*)d_in[0], (const uint8_t*)d_in[1], (const uint8_t*)d_in[2],
                                                   (const uint8_t*)d_in[3], (const uint8_t*)d_in[4], (__nv_bfloat16*)d_out);
}
```

```cpp
#include <cuda_runtime.h>
#include <cuda_bf16.h>
#include <cuda.h>
#include <stdint.h>

namespace {

constexpr int B_ = 16, SQ = 112, DM = 576, HQ = 32, HKV = 16, SK = 512, DH = 128;
constexpr int NSLOT = 6;
constexpr int SLOT_BYTES = 16384;
constexpr int BLK = 112 * 128;
constexpr int NFILL_Q = 36, NFILL_KV = 32, NFILL_O = 36;
constexpr int FILL_KV0 = NFILL_Q, FILL_O0 = NFILL_Q + NFILL_KV, NFILL = FILL_O0 + NFILL_O;
constexpr int OFF_SLOTS = 8 * BLK;
constexpr int OFF_STAGE = OFF_SLOTS + NSLOT * SLOT_BYTES;
constexpr int OFF_BARS = OFF_STAGE + BLK;
constexpr int NBARS = 2 * NFILL + 9 + 1;
constexpr int SMEM_BYTES = OFF_BARS + NBARS * 8 + 64;
constexpr int NTHREADS = 384;
constexpr int PF_DIST = 10, PF_Q0 = 6, PF_QS = 6, PF_LAG = 3, PF_SPAN = 27;
constexpr uint32_t SPIN_LIMIT = 1u << 22;

__device__ uint4 g_part[B_ * 8 * 8 * 8 * 128];
__device__ uint4 g_part8[B_ * 8 * 8 * 4 * 32];
__device__ uint32_t g_epoch[B_];

#define TSTAMP(i) do {} while (0)

__device__ __forceinline__ uint32_t smem_u32(const void* p) { return (uint32_t)__cvta_generic_to_shared(p); }
__device__ __forceinline__ void mbar_init(uint32_t bar, uint32_t cnt) { asm volatile("mbarrier.init.shared::cta.b64 [%0], %1;" ::"r"(bar), "r"(cnt) : "memory"); }
__device__ __forceinline__ void mbar_expect_tx(uint32_t bar, uint32_t bytes) { asm volatile("mbarrier.arrive.expect_tx.shared::cta.b64 _, [%0], %1;" ::"r"(bar), "r"(bytes) : "memory"); }
__device__ __forceinline__ void mbar_arrive_pred(uint32_t bar, bool p) { asm volatile("{\n.reg .pred p;\nsetp.ne.b32 p, %1, 0;\n@p mbarrier.arrive.shared::cta.b64 _, [%0];\n}\n" ::"r"(bar), "r"((int)p) : "memory"); }
__device__ __forceinline__ void mbar_arrive_remote_pred(uint32_t rbar, bool p) { asm volatile("{\n.reg .pred p;\nsetp.ne.b32 p, %1, 0;\n@p mbarrier.arrive.shared::cluster.b64 _, [%0];\n}\n" ::"r"(rbar), "r"((int)p) : "memory"); }
__device__ __forceinline__ void mbar_wait_sleep(uint32_t bar) {
  uint32_t done, it = 0;
  do {
    asm volatile("{\n.reg .pred p;\nmbarrier.try_wait.parity.shared::cta.b64 p, [%1], 0, %2;\nselp.u32 %0, 1, 0, p;\n}\n" : "=r"(done) : "r"(bar), "r"(100000u) : "memory");
    if (++it > 4096) break;
  } while (!done);
}
__device__ __forceinline__ void mbar_wait(uint32_t bar) {
  asm volatile("{\n.reg .pred p;\n.reg .u32 c;\n"
               "mbarrier.try_wait.parity.shared::cta.b64 p, [%0], 0;\n@p bra.uni DONE;\nmov.u32 c, 0;\n"
               "LOOP:\nmbarrier.try_wait.parity.shared::cta.b64 p, [%0], 0;\n@p bra.uni DONE;\n"
               "add.u32 c, c, 1;\nsetp.lt.u32 p, c, %1;\n@p bra.uni LOOP;\nDONE:\n}\n" ::"r"(bar), "n"(SPIN_LIMIT) : "memory");
}
__device__ __forceinline__ uint32_t mapa(uint32_t addr, uint32_t cta) { uint32_t r; asm volatile("mapa.shared::cluster.u32 %0, %1, %2;" : "=r"(r) : "r"(addr), "r"(cta)); return r; }
__device__ __forceinline__ void tma_2d(uint32_t dst, const CUtensorMap* m, int c0, int c1, uint32_t bar) {
  asm volatile("cp.async.bulk.tensor.2d.shared::cluster.global.mbarrier::complete_tx::bytes [%0], [%1, {%3, %4}], [%2];" ::"r"(dst), "l"(m), "r"(bar), "r"(c0), "r"(c1) : "memory");
}
__device__ __forceinline__ void tma_2d_mc(uint32_t dst, const CUtensorMap* m, int c0, int c1, uint32_t bar) {
  asm volatile("cp.async.bulk.tensor.2d.shared::cluster.global.mbarrier::complete_tx::bytes.multicast::cluster [%0], [%1, {%3, %4}], [%2], %5;" ::"r"(dst), "l"(m), "r"(bar), "r"(c0), "r"(c1), "h"((uint16_t)3) : "memory");
}
__device__ __forceinline__ void tma_3d(uint32_t dst, const CUtensorMap* m, int c0, int c1, int c2, uint32_t bar) {
  asm volatile("cp.async.bulk.tensor.3d.shared::cluster.global.mbarrier::complete_tx::bytes [%0], [%1, {%3, %4, %5}], [%2];" ::"r"(dst), "l"(m), "r"(bar), "r"(c0), "r"(c1), "r"(c2) : "memory");
}
__device__ __forceinline__ uint4 ld_relaxed_b128(const uint4* p) {
  uint4 v;
  asm volatile("{\n.reg .b64 l, h;\n.reg .b128 t;\nld.relaxed.gpu.global.b128 t, [%4];\nmov.b128 {l, h}, t;\n"
               "mov.b64 {%0, %1}, l;\nmov.b64 {%2, %3}, h;\n}\n" : "=r"(v.x), "=r"(v.y), "=r"(v.z), "=r"(v.w) : "l"(p) : "memory");
  return v;
}
__device__ __forceinline__ void l2_prefetch(const void* p, uint32_t bytes) { asm volatile("cp.async.bulk.prefetch.L2.global [%0], %1;" ::"l"(p), "r"(bytes) : "memory"); }
__device__ __forceinline__ void prefetch_line(const void* p) { asm volatile("prefetch.global.L2 [%0];" ::"l"(p)); }
__device__ __forceinline__ void prefetch_tmap(const CUtensorMap* m) { asm volatile("prefetch.tensormap [%0];" ::"l"(m) : "memory"); }
__device__ __forceinline__ bool elect_one() { uint32_t p; asm volatile("{\n.reg .pred p;\nelect.sync _|p, 0xffffffff;\nselp.u32 %0, 1, 0, p;\n}\n" : "=r"(p)); return p != 0; }
__device__ __forceinline__ void named_bar(int id, int n) { asm volatile("bar.sync %0, %1;" ::"r"(id), "r"(n) : "memory"); }
__device__ __forceinline__ void named_arrive(int id, int n) { asm volatile("bar.arrive %0, %1;" ::"r"(id), "r"(n) : "memory"); }
__device__ __forceinline__ void fence_async_smem() { asm volatile("fence.proxy.async.shared::cta;" ::: "memory"); }
#define WG_FENCE() asm volatile("wgmma.fence.sync.aligned;" ::: "memory")
#define WG_COMMIT() asm volatile("wgmma.commit_group.sync.aligned;" ::: "memory")
#define WG_WAIT(n) asm volatile("wgmma.wait_group.sync.aligned %0;" ::"n"(n) : "memory")
template <int N> __device__ __forceinline__ void pin(float (&d)[N]) {
#pragma unroll
  for (int i = 0; i < N; i++) asm volatile("" : "+f"(d[i])::"memory");
}
__device__ __forceinline__ uint64_t mkdesc(uint32_t lo) { return ((uint64_t)(64u | (1u << 30)) << 32) | lo; }
__device__ __forceinline__ uint32_t pack_bf16(float lo, float hi) { uint32_t r; asm("cvt.rn.bf16x2.f32 %0, %1, %2;" : "=r"(r) : "f"(hi), "f"(lo)); return r; }
__device__ __forceinline__ float ex2(float x) { float r; asm("ex2.approx.ftz.f32 %0, %1;" : "=f"(r) : "f"(x)); return r; }
__device__ __forceinline__ float rcp_fast(float x) { float r; asm("rcp.approx.ftz.f32 %0, %1;" : "=f"(r) : "f"(x)); return r; }
__device__ __forceinline__ void stsm_x4(uint32_t addr, uint32_t r0, uint32_t r1, uint32_t r2, uint32_t r3) {
  asm volatile("stmatrix.sync.aligned.m8n8.x4.shared.b16 [%0], {%1, %2, %3, %4};" ::"r"(addr), "r"(r0), "r"(r1), "r"(r2), "r"(r3) : "memory");
}
__device__ __forceinline__ void stsm_x4_t(uint32_t addr, uint32_t r0, uint32_t r1, uint32_t r2, uint32_t r3) {
  asm volatile("stmatrix.sync.aligned.m8n8.x4.trans.shared.b16 [%0], {%1, %2, %3, %4};" ::"r"(addr), "r"(r0), "r"(r1), "r"(r2), "r"(r3) : "memory");
}

__device__ __forceinline__ void wgmma_n112_ta(float (&d)[56], uint64_t da, uint64_t db, int sc) {
  asm volatile("{\n.reg .pred p;\nsetp.ne.b32 p, %58, 0;\n"
    "wgmma.mma_async.sync.aligned.m64n112k16.f32.bf16.bf16 "
    "{%0, %1, %2, %3, %4, %5, %6, %7, %8, %9, %10, %11, %12, %13, %14, %15, %16, %17, %18, %19, %20, %21, %22, %23, %24, %25, %26, %27, %28, %29, %30, %31, %32, %33, %34, %35, %36, %37, %38, %39, %40, %41, %42, %43, %44, %45, %46, %47, %48, %49, %50, %51, %52, %53, %54, %55}, "
    "%56, %57, p, 1, 1, 1, 0;\n}\n"
    : "+f"(d[0]), "+f"(d[1]), "+f"(d[2]), "+f"(d[3]), "+f"(d[4]), "+f"(d[5]), "+f"(d[6]), "+f"(d[7]), "+f"(d[8]), "+f"(d[9]), "+f"(d[10]), "+f"(d[11]), "+f"(d[12]), "+f"(d[13]), "+f"(d[14]), "+f"(d[15]), "+f"(d[16]), "+f"(d[17]), "+f"(d[18]), "+f"(d[19]), "+f"(d[20]), "+f"(d[21]), "+f"(d[22]), "+f"(d[23]), "+f"(d[24]), "+f"(d[25]), "+f"(d[26]), "+f"(d[27]), "+f"(d[28]), "+f"(d[29]), "+f"(d[30]), "+f"(d[31]), "+f"(d[32]), "+f"(d[33]), "+f"(d[34]), "+f"(d[35]), "+f"(d[36]), "+f"(d[37]), "+f"(d[38]), "+f"(d[39]), "+f"(d[40]), "+f"(d[41]), "+f"(d[42]), "+f"(d[43]), "+f"(d[44]), "+f"(d[45]), "+f"(d[46]), "+f"(d[47]), "+f"(d[48]), "+f"(d[49]), "+f"(d[50]), "+f"(d[51]), "+f"(d[52]), "+f"(d[53]), "+f"(d[54]), "+f"(d[55])
    : "l"(da), "l"(db), "r"(sc));
}

__device__ __forceinline__ void wgmma_n64_ss(float (&d)[32], uint64_t da, uint64_t db, int sc) {
  asm volatile("{\n.reg .pred p;\nsetp.ne.b32 p, %34, 0;\n"
    "wgmma.mma_async.sync.aligned.m64n64k16.f32.bf16.bf16 "
    "{%0, %1, %2, %3, %4, %5, %6, %7, %8, %9, %10, %11, %12, %13, %14, %15, %16, %17, %18, %19, %20, %21, %22, %23, %24, %25, %26, %27, %28, %29, %30, %31}, "
    "%32, %33, p, 1, 1, 0, 0;\n}\n"
    : "+f"(d[0]), "+f"(d[1]), "+f"(d[2]), "+f"(d[3]), "+f"(d[4]), "+f"(d[5]), "+f"(d[6]), "+f"(d[7]), "+f"(d[8]), "+f"(d[9]), "+f"(d[10]), "+f"(d[11]), "+f"(d[12]), "+f"(d[13]), "+f"(d[14]), "+f"(d[15]), "+f"(d[16]), "+f"(d[17]), "+f"(d[18]), "+f"(d[19]), "+f"(d[20]), "+f"(d[21]), "+f"(d[22]), "+f"(d[23]), "+f"(d[24]), "+f"(d[25]), "+f"(d[26]), "+f"(d[27]), "+f"(d[28]), "+f"(d[29]), "+f"(d[30]), "+f"(d[31])
    : "l"(da), "l"(db), "r"(sc));
}

__device__ __forceinline__ void wgmma_n128_rs(float (&d)[64], uint32_t a0, uint32_t a1, uint32_t a2, uint32_t a3, uint64_t db, int sc) {
  asm volatile("{\n.reg .pred p;\nsetp.ne.b32 p, %69, 0;\n"
    "wgmma.mma_async.sync.aligned.m64n128k16.f32.bf16.bf16 "
    "{%0, %1, %2, %3, %4, %5, %6, %7, %8, %9, %10, %11, %12, %13, %14, %15, %16, %17, %18, %19, %20, %21, %22, %23, %24, %25, %26, %27, %28, %29, %30, %31, %32, %33, %34, %35, %36, %37, %38, %39, %40, %41, %42, %43, %44, %45, %46, %47, %48, %49, %50, %51, %52, %53, %54, %55, %56, %57, %58, %59, %60, %61, %62, %63}, "
    "{%64, %65, %66, %67}, %68, p, 1, 1, 1;\n}\n"
    : "+f"(d[0]), "+f"(d[1]), "+f"(d[2]), "+f"(d[3]), "+f"(d[4]), "+f"(d[5]), "+f"(d[6]), "+f"(d[7]), "+f"(d[8]), "+f"(d[9]), "+f"(d[10]), "+f"(d[11]), "+f"(d[12]), "+f"(d[13]), "+f"(d[14]), "+f"(d[15]), "+f"(d[16]), "+f"(d[17]), "+f"(d[18]), "+f"(d[19]), "+f"(d[20]), "+f"(d[21]), "+f"(d[22]), "+f"(d[23]), "+f"(d[24]), "+f"(d[25]), "+f"(d[26]), "+f"(d[27]), "+f"(d[28]), "+f"(d[29]), "+f"(d[30]), "+f"(d[31]), "+f"(d[32]), "+f"(d[33]), "+f"(d[34]), "+f"(d[35]), "+f"(d[36]), "+f"(d[37]), "+f"(d[38]), "+f"(d[39]), "+f"(d[40]), "+f"(d[41]), "+f"(d[42]), "+f"(d[43]), "+f"(d[44]), "+f"(d[45]), "+f"(d[46]), "+f"(d[47]), "+f"(d[48]), "+f"(d[49]), "+f"(d[50]), "+f"(d[51]), "+f"(d[52]), "+f"(d[53]), "+f"(d[54]), "+f"(d[55]), "+f"(d[56]), "+f"(d[57]), "+f"(d[58]), "+f"(d[59]), "+f"(d[60]), "+f"(d[61]), "+f"(d[62]), "+f"(d[63])
    : "r"(a0), "r"(a1), "r"(a2), "r"(a3), "l"(db), "r"(sc));
}

template <int I0 = 0, int I1 = 7>
__device__ __forceinline__ void store_tile_t(uint32_t blk, const uint32_t (&pk)[28], int wi, int lane) {
  const int mi = lane >> 3, r = lane & 7;
  const uint32_t base = blk + (uint32_t)(((mi >> 1) * 8 + r) * 128 + (((2 * wi + (mi & 1)) ^ r) << 4));
#pragma unroll
  for (int i = I0; i < I1; i++) stsm_x4_t(base + i * 2048, pk[4 * i], pk[4 * i + 1], pk[4 * i + 2], pk[4 * i + 3]);
}
__device__ __forceinline__ void pack_tile(uint32_t (&pk)[28], const float (&a)[56]) {
#pragma unroll
  for (int i = 0; i < 28; i++) pk[i] = pack_bf16(a[2 * i], a[2 * i + 1]);
}

constexpr float SCALE_LOG2E = 0.08838834764831845f * 1.4426950408889634f;
__device__ __forceinline__ void pack_tile_scaled(uint32_t (&pk)[28], const float (&a)[56]) {
#pragma unroll
  for (int i = 0; i < 28; i++) pk[i] = pack_bf16(a[2 * i] * SCALE_LOG2E, a[2 * i + 1] * SCALE_LOG2E);
}

struct RowStat { float m0, m1, l0, l1; };

__device__ __forceinline__ void finish_rows(RowStat& st) {
  float l0 = st.l0, l1 = st.l1;
  l0 += __shfl_xor_sync(0xffffffffu, l0, 1); l1 += __shfl_xor_sync(0xffffffffu, l1, 1);
  l0 += __shfl_xor_sync(0xffffffffu, l0, 2); l1 += __shfl_xor_sync(0xffffffffu, l1, 2);
  st.l0 = rcp_fast(l0); st.l1 = rcp_fast(l1);
}
__device__ __forceinline__ void store_o_tile(uint32_t blk0, int row0, float (&O)[64], const RowStat& st) {
  int tid_;
  asm volatile("mov.u32 %0, %%tid.x;" : "=r"(tid_));
  const int lane = tid_ & 31, wi = (tid_ >> 5) & 3;
  const float i0 = st.l0, i1 = st.l1;
  const int mi = lane >> 3, r = lane & 7;
  const uint32_t base = blk0 + (uint32_t)((row0 + 16 * wi + (mi & 1) * 8 + r) * 128);
#pragma unroll
  for (int i = 0; i < 16; i += 2) {
    const int cg = (i & 7) + (mi >> 1);
    const uint32_t addr = base + (uint32_t)((i >> 3) * BLK) + (uint32_t)((cg ^ r) << 4);
    const uint32_t w0 = pack_bf16(O[4 * i] * i0, O[4 * i + 1] * i0), w1 = pack_bf16(O[4 * i + 2] * i1, O[4 * i + 3] * i1);
    const uint32_t w2 = pack_bf16(O[4 * i + 4] * i0, O[4 * i + 5] * i0), w3 = pack_bf16(O[4 * i + 6] * i1, O[4 * i + 7] * i1);
    stsm_x4(addr, w0, w1, w2, w3);
  }
}

constexpr float SUM_HI = 16777216.0f, SUM_HI_LOG2 = 24.0f, SUM_LO = 1.0f / 16777216.0f;
__device__ __forceinline__ void sub_ref(float (&S)[32], const RowStat& st) {
#pragma unroll
  for (int i = 0; i < 8; i++) { S[4 * i] -= st.m0; S[4 * i + 1] -= st.m0; S[4 * i + 2] -= st.m1; S[4 * i + 3] -= st.m1; }
}
__device__ __forceinline__ void update_ref(float (&T)[32], float (&O)[64], RowStat& st, bool first) {
  float a0 = fmaxf(T[0], T[1]), a1 = fmaxf(T[2], T[3]), b0 = fmaxf(T[4], T[5]), b1 = fmaxf(T[6], T[7]);
#pragma unroll
  for (int i = 2; i < 8; i += 2) {
    a0 = fmaxf(a0, fmaxf(T[4 * i], T[4 * i + 1])); a1 = fmaxf(a1, fmaxf(T[4 * i + 2], T[4 * i + 3]));
    b0 = fmaxf(b0, fmaxf(T[4 * i + 4], T[4 * i + 5])); b1 = fmaxf(b1, fmaxf(T[4 * i + 6], T[4 * i + 7]));
  }
  float d0 = fmaxf(a0, b0), d1 = fmaxf(a1, b1);
  d0 = fmaxf(d0, __shfl_xor_sync(0xffffffffu, d0, 1)); d1 = fmaxf(d1, __shfl_xor_sync(0xffffffffu, d1, 1));
  d0 = fmaxf(d0, __shfl_xor_sync(0xffffffffu, d0, 2)); d1 = fmaxf(d1, __shfl_xor_sync(0xffffffffu, d1, 2));
  if (first) {
    st.m0 = d0; st.m1 = d1;
  } else {
    d0 = fmaxf(d0, 0.f); d1 = fmaxf(d1, 0.f);
    const float r0 = ex2(-d0), r1 = ex2(-d1);
    st.m0 += d0; st.m1 += d1; st.l0 *= r0; st.l1 *= r1;
#pragma unroll
    for (int i = 0; i < 16; i++) { O[4 * i] *= r0; O[4 * i + 1] *= r0; O[4 * i + 2] *= r1; O[4 * i + 3] *= r1; }
  }
#pragma unroll
  for (int i = 0; i < 8; i++) { T[4 * i] -= d0; T[4 * i + 1] -= d0; T[4 * i + 2] -= d1; T[4 * i + 3] -= d1; }
}
__device__ __forceinline__ bool softmax_exp(const float (&T)[32], uint32_t (&P)[16], float& l0, float& l1, float lo) {
  const bool ok_last = fmaxf(fmaxf(T[28], T[29]), fmaxf(T[30], T[31])) <= SUM_HI_LOG2;
  bool bad = false;
#pragma unroll
  for (int i = 0; i < 8; i++) {
    if (i == 7) bad = __any_sync(0xffffffffu, !(fmaxf(l0, l1) <= SUM_HI && fminf(l0, l1) >= lo && ok_last));
    const float p0 = ex2(T[4 * i]), p1 = ex2(T[4 * i + 1]), p2 = ex2(T[4 * i + 2]), p3 = ex2(T[4 * i + 3]);
    if (i == 0) { l0 = p0; l1 = p2; } else { l0 += p0; l1 += p2; }
    l0 += p1; l1 += p3;
    P[2 * i] = pack_bf16(p0, p1); P[2 * i + 1] = pack_bf16(p2, p3);
  }
  return bad;
}
__device__ __forceinline__ void softmax_tile(float (&T)[32], float (&O)[64], uint32_t (&P)[16], RowStat& st, bool& sub, bool first) {
  float l0, l1;
  if (__builtin_expect(softmax_exp(T, P, l0, l1, first ? SUM_LO : 0.f), 0)) {
    update_ref(T, O, st, first);
    sub = true;
    softmax_exp(T, P, l0, l1, 0.f);
  }
  st.l0 += l0; st.l1 += l1;
}

__device__ __forceinline__ void issue_s(float (&S)[32], uint32_t q16, uint32_t k16) {
  const uint64_t dq = mkdesc(q16), dk = mkdesc(k16);
#pragma unroll
  for (int kk = 0; kk < 8; kk++)
    wgmma_n64_ss(S, dq + ((kk >> 2) * (BLK / 16) + (kk & 3) * 2), dk + ((kk >> 2) * 512 + (kk & 3) * 2), kk != 0);
}
__device__ __forceinline__ void issue_pv(float (&O)[64], const uint32_t (&P)[16], uint32_t v16, int acc) {
  const uint64_t dv = mkdesc(v16 + (512u << 16));
#pragma unroll
  for (int kk = 0; kk < 4; kk++)
    wgmma_n128_rs(O, P[4 * kk], P[4 * kk + 1], P[4 * kk + 2], P[4 * kk + 3], dv + kk * 128, kk ? 1 : acc);
}

__device__ __forceinline__ int o_tile_of_step(int j, int s) { return s == 7 ? 8 : ((j + 1 + s - (s == 8)) & 7); }
__device__ __forceinline__ int o_quarter(int kq) { return ((kq & 1) << 1) | (kq >> 1); }

__device__ __forceinline__ void store_chunk(uint4* p, const float* a, float tagf) {
  asm volatile("st.relaxed.gpu.global.v4.b32 [%0], {%1, %2, %3, %4};" ::"l"(p), "r"(pack_bf16(a[0], a[1])),
               "r"(pack_bf16(a[2], a[3])), "r"(pack_bf16(a[4], a[5])), "r"(pack_bf16(a[6], tagf)) : "memory");
}
__device__ __forceinline__ void add_chunk(float* a, const uint4& v) {
  a[0] += __uint_as_float(v.x << 16); a[1] += __uint_as_float(v.x & 0xffff0000u);
  a[2] += __uint_as_float(v.y << 16); a[3] += __uint_as_float(v.y & 0xffff0000u);
  a[4] += __uint_as_float(v.z << 16); a[5] += __uint_as_float(v.z & 0xffff0000u);
  a[6] += __uint_as_float(v.w << 16);
}
__device__ __forceinline__ void load_chunks(uint4 (&v)[8], const uint4* p, int stride) {
#pragma unroll
  for (int i = 0; i < 8; i++) v[i] = ld_relaxed_b128(p + i * stride);
}
__device__ __forceinline__ void check_chunks(uint4 (&v)[8], const uint4* p, int stride, uint32_t tagbits) {
  uint32_t it = 0;
  for (;;) {
    uint32_t bad = 0;
#pragma unroll
    for (int i = 0; i < 8; i++) bad |= v[i].w ^ tagbits;
    if (!__any_sync(0xffffffffu, bad > 0xffffu) || ++it > SPIN_LIMIT) break;
    load_chunks(v, p, stride);
  }
}
__device__ __forceinline__ void add_partial(float (&a)[56], uint4 (&v)[8], const uint4* p, uint32_t tagbits) {
  check_chunks(v, p, 128, tagbits);
#pragma unroll
  for (int i = 0; i < 8; i++) add_chunk(a + 7 * i, v[i]);
}

__host__ __device__ constexpr uint32_t bar_count(int i) {
  return i >= 2 * NFILL ? 1
       : i >= NFILL ? ((i - NFILL >= FILL_O0 - NSLOT && i - NFILL < FILL_O0) ? 16 : 8)
       : (i > FILL_KV0 && i < FILL_O0 - 1) ? 2 : 1;
}
template <int W> __device__ __forceinline__ void init_barriers(uint32_t base, int w) {
  constexpr int NW = NTHREADS / 32 - 1, PER = (NBARS + NW - 1) / NW;
  if (w == W) {
#pragma unroll
    for (int i = W * PER; i < (W + 1) * PER && i < NBARS; i++)
      if (i > 1 && i != 2 * NFILL && i != 2 * NFILL + 1) mbar_init(base + i * 8, bar_count(i));
  } else if constexpr (W + 1 < NW) {
    init_barriers<W + 1>(base, w);
  }
}

__global__ void __cluster_dims__(2, 1, 1) __launch_bounds__(NTHREADS, 1)
gqa_fused_kernel(const __grid_constant__ CUtensorMap tm_x, const __grid_constant__ CUtensorMap tm_k,
                 const __grid_constant__ CUtensorMap tm_v, const __grid_constant__ CUtensorMap tm_wq,
                 const __grid_constant__ CUtensorMap tm_wo, const uint8_t* __restrict__ gx,
                 const uint8_t* __restrict__ gk, const uint8_t* __restrict__ gv, const uint8_t* __restrict__ gwq,
                 const uint8_t* __restrict__ gwo, __nv_bfloat16* __restrict__ gout) {
  extern __shared__ __align__(1024) uint8_t smem[];
  const uint32_t sb = smem_u32(smem);
  const uint32_t slots = sb + OFF_SLOTS;
  const uint32_t bar_full = sb + OFF_BARS, bar_empty = bar_full + NFILL * 8, bar_x = bar_empty + NFILL * 8, bar_tag = bar_x + 9 * 8,
                 s_tag = bar_tag + 8, stage = sb + OFF_STAGE;
  const int tid = threadIdx.x, lane = tid & 31;
  const int wg = __shfl_sync(0xffffffffu, tid >> 7, 0), wi = __shfl_sync(0xffffffffu, (tid >> 5) & 3, 0);
  const uint32_t rank = blockIdx.x & 1;
  const int cl = blockIdx.x >> 1;
  const int j = cl & 7, b = (cl >> 3) * 2 + (int)rank;

  TSTAMP(0);
  if (tid < 32) prefetch_line(gwq + (size_t)(64 + b * 8 + (tid >> 2)) * (HQ * DH * 2) + j * 1024 + (tid & 3) * 128);
  else if (tid < 60) prefetch_line(gx + (size_t)(b * SQ + j * 14 + ((tid - 32) >> 1)) * (DM * 2) + 256 + (tid & 1) * 128);
  if (tid == 256) {
    mbar_init(bar_full, 1); mbar_init(bar_full + 8, 1); mbar_init(bar_x, 1); mbar_init(bar_x + 8, 1);
    asm volatile("fence.mbarrier_init.release.cluster;" ::: "memory");
    fence_async_smem();
    mbar_expect_tx(bar_x, BLK);
    tma_2d(sb, &tm_x, 0, b * SQ, bar_x);
#pragma unroll
    for (int w = 0; w < 2; w++) {
      mbar_expect_tx(bar_full + w * 8, SLOT_BYTES);
      tma_2d(slots + w * SLOT_BYTES, &tm_wq, (4 * j + w) * DH, 0, bar_full + w * 8);
      tma_2d(slots + w * SLOT_BYTES + 8192, &tm_wq, (4 * j + w) * DH + 64, 0, bar_full + w * 8);
    }
    mbar_expect_tx(bar_x + 8, BLK);
    tma_2d(sb + BLK, &tm_x, 64, b * SQ, bar_x + 8);
  } else if (lane == 0) {
    init_barriers<0>(bar_full, wg * 4 + wi - (wg == 2));
    asm volatile("fence.mbarrier_init.release.cluster;" ::: "memory");
    if (tid == 288) { prefetch_tmap(&tm_k); prefetch_tmap(&tm_v); prefetch_tmap(&tm_wo); }
  }
  __syncwarp();
  __syncthreads();
  asm volatile("barrier.cluster.arrive.relaxed.aligned;" ::: "memory");
  __syncwarp();
  asm volatile("barrier.cluster.wait.acquire.aligned;" ::: "memory");

  if (wg == 2) {
    asm volatile("setmaxnreg.dec.sync.aligned.u32 24;");
    if (wi < 2) {
      const uint32_t slot0 = slots + wi * SLOT_BYTES;
      uint32_t dst = slot0, fb = bar_full + wi * 8;
      auto next = [&]() { dst = (dst == slot0 + 4 * SLOT_BYTES) ? slot0 : dst + 2 * SLOT_BYTES; fb += 16; };
      constexpr uint32_t EMPTY_OFF = NFILL * 8 - NSLOT * 8;
      int c0 = (4 * j + wi) * DH + (int)rank * 64;
      next();
#pragma unroll 1
      for (int t = 1; t < 18; t++) {
        const int k = t < 9 ? t : t - 9;
        if (t == 9) c0 += 2 * DH;
        if (t >= 3) mbar_wait_sleep(fb + EMPTY_OFF);
        if (elect_one()) {
          mbar_expect_tx(fb, SLOT_BYTES);
          tma_2d_mc(dst + rank * 8192, &tm_wq, c0, k * 64, fb);
          if (t < 8 && wi == 1) {
            mbar_expect_tx(bar_x + (t + 1) * 8, BLK);
            tma_2d(t < 7 ? sb + (t + 1) * BLK : stage, &tm_x, (t + 1) * 64, b * SQ, bar_x + (t + 1) * 8);
          }
        }
        next();
      }
      fb += 16 * 16;
      dst = slot0 + (FILL_O0 % NSLOT) * SLOT_BYTES;
      const int r0 = j * 512 + wi * 256 + (int)rank * 64;
#pragma unroll 1
      for (int t = 0; t < 18; t++) {
        mbar_wait_sleep(fb + EMPTY_OFF + ((wi && t < 2) ? 8 : 0));
        const int cw = o_tile_of_step(j, t >> 1) * 64;
        if (elect_one()) {
          mbar_expect_tx(fb, SLOT_BYTES);
          tma_2d_mc(dst + rank * 8192, &tm_wo, cw, r0 + (t & 1) * 128, fb);
        }
        next();
      }
    } else if (wi == 2) {
      const size_t kv0 = (size_t)(b * HKV + 2 * j) * SK * DH * 2;
#pragma unroll 1
      for (int c = 0; c < PF_DIST; c++) {
        mbar_wait_sleep(bar_full + (PF_Q0 + (c * PF_QS) / 2) * 8);
        if (elect_one()) l2_prefetch(((c & 1) ? gv : gk) + kv0 + (size_t)(c >> 1) * 16384, 16384);
      }
    } else if (wi == 3) {
      const uint8_t* wq0 = gwq + (size_t)b * (HQ * DH * 2) + j * 1024 + (lane & 3) * 128;
#pragma unroll
      for (int i = 0; i < 3; i++) prefetch_line(wq0 + (size_t)(192 + 16 * (i * 8 + (lane >> 2))) * (HQ * DH * 2));
      if ((lane & 15) < 14) {
        const uint8_t* xr = gx + (size_t)(b * SQ + j * 14 + (lane & 15)) * (DM * 2) + (4 + (lane >> 4)) * 128;
        prefetch_line(xr); prefetch_line(xr + 256);
        if (lane < 16) prefetch_line(xr + 512);
      }
      mbar_wait_sleep(bar_full + 2 * 8);
#pragma unroll
      for (int i = 0; i < 5; i++)
        if (i * 8 + (lane >> 2) < 36) prefetch_line(wq0 + 512 + (size_t)(16 * (i * 8 + (lane >> 2))) * (HQ * DH * 2));
      if (lane == 0) {
        const uint32_t e = *reinterpret_cast<volatile uint32_t*>(g_epoch + b);
        asm volatile("st.shared.u32 [%0], %1;" ::"r"(s_tag), "r"((0x0800u + e % 0x7000u) << 16) : "memory");
        mbar_arrive_pred(bar_tag, true);
      }
      __syncwarp();
      const int row0 = (b * HKV + 2 * j) * SK;
      const size_t kv0 = (size_t)(b * HKV + 2 * j) * SK * DH * 2;
      uint32_t dst = slots;
      int pf = PF_DIST, acc = 0;
#pragma unroll 1
      for (int c = 0; c < 32; c++) {
        if (c < 7 || (c & 1)) mbar_wait_sleep(bar_empty + (FILL_KV0 - NSLOT + c + (c >= 7)) * 8);
        const uint32_t f = bar_full + (FILL_KV0 + c - ((c > 0 && !(c & 1)) ? 1 : 0)) * 8;
        acc += (c >= PF_LAG) ? 32 - PF_DIST : 0;
        const bool dopf = acc >= PF_SPAN && pf < 32;
        if (elect_one()) {
          mbar_expect_tx(f, SLOT_BYTES);
          tma_3d(dst, (c & 1) ? &tm_v : &tm_k, 0, row0 + (c >> 1) * 64, 0, f);
          if (dopf) l2_prefetch(((pf & 1) ? gv : gk) + kv0 + (size_t)(pf >> 1) * 16384, 16384);
          if (c >= 29) l2_prefetch(gwo + (size_t)j * (512 * DM * 2) + (size_t)b * 36864 + (c - 29) * 12288, 12288);
        }
        if (dopf) { pf++; acc -= PF_SPAN; }
        dst = (dst == slots + 5 * SLOT_BYTES) ? slots : dst + SLOT_BYTES;
      }
    }
  } else {
    asm volatile("setmaxnreg.inc.sync.aligned.u32 240;");
    const uint32_t peer_empty = mapa(bar_empty, rank ^ 1);
    const uint32_t dsb = (sb & 0x3FFFF) >> 4, dslots = dsb + OFF_SLOTS / 16;
    constexpr uint32_t BLK16 = BLK / 16, SLOT16 = SLOT_BYTES / 16;
    auto release_both = [&](int n) { mbar_arrive_pred(bar_empty + n * 8, lane == 0); mbar_arrive_remote_pred(peer_empty + n * 8, lane == 0); };
    auto release_kv = [&](int n) {
      mbar_arrive_pred(bar_empty + n * 8, lane == 0);
      mbar_arrive_remote_pred(peer_empty + n * 8, lane == 0 && n >= FILL_O0 - NSLOT);
    };
    TSTAMP(1);
    const uint32_t qblk = sb + (2 * wg) * BLK, dq = dsb + (2 * wg) * BLK16;
    float Sa[32];
    {
      float acc0[56], acc1[56];
      uint32_t q0[28], q1[28];
      if (wg == 1) named_arrive(4, 256);
      uint32_t qs = dslots + wg * SLOT16;
      auto q_step = [&](int n, int k) {
        const uint64_t da = mkdesc(qs), db = mkdesc(dsb + (k < 8 ? k * BLK16 : OFF_STAGE / 16));
        mbar_wait(bar_full + n * 8);
        named_bar(4 + wg, 256);
        WG_FENCE();
#pragma unroll
        for (int kk = 0; kk < 4; kk++) {
          wgmma_n112_ta(acc0, da + kk * 128, db + kk * 2, (k | kk) != 0);
          wgmma_n112_ta(acc1, da + (512 + kk * 128), db + kk * 2, (k | kk) != 0);
        }
        WG_COMMIT();
        named_arrive(4 + (wg ^ 1), 256);
        qs = (qs >= dslots + 4 * SLOT16) ? qs - 4 * SLOT16 : qs + 2 * SLOT16;
        if (k > 0) { WG_WAIT(1); release_both(n - 2); }
      };
#pragma unroll 1
      for (int k = 0; k < 9; k++) {
        mbar_wait(bar_x + k * 8);
        q_step(k * 2 + wg, k);
      }
      WG_WAIT(0);
      release_both(16 + wg);
      pin(acc0); pin(acc1);
      pack_tile_scaled(q0, acc0); pack_tile_scaled(q1, acc1);
#pragma unroll 1
      for (int k = 0; k < 9; k++) {
        q_step(18 + k * 2 + wg, k);
        if (k == 4 + wg) store_tile_t<0, 4>(qblk, q0, wi, lane);
        if (k == 5 + wg) store_tile_t<4, 7>(qblk, q0, wi, lane);
        if (k == 6 + wg) store_tile_t<0, 4>(qblk + BLK, q1, wi, lane);
        if (k == 7 + wg) store_tile_t<4, 7>(qblk + BLK, q1, wi, lane);
      }
      TSTAMP(2);
      WG_WAIT(0);
      release_both(34 + wg);
      fence_async_smem();
      mbar_wait(bar_full + FILL_KV0 * 8);
      named_bar(4 + wg, 256);
      WG_FENCE();
      issue_s(Sa, dq, dslots + (FILL_KV0 % NSLOT) * SLOT16);
      WG_COMMIT();
      named_arrive(4 + (wg ^ 1), 256);
      pin(acc0); pin(acc1);
      pack_tile_scaled(q0, acc0); pack_tile_scaled(q1, acc1);
      store_tile_t(qblk + 4 * BLK, q0, wi, lane);
      store_tile_t(qblk + 5 * BLK, q1, wi, lane);
    }
    TSTAMP(3);
    {
      float Oa[64], Ob[64], Sb[32];
      uint32_t P[16];
      RowStat sa, sbt;
      WG_WAIT(0);
      fence_async_smem();
      sa.m0 = sa.m1 = sbt.m0 = sbt.m1 = 0.f; sa.l0 = sa.l1 = sbt.l0 = sbt.l1 = 0.f;
      int slot_k = FILL_KV0 % NSLOT;
      bool suba = false, subb = false;
      uint32_t vprev = dslots + slot_k * SLOT16;
#pragma unroll 1
      for (int jj = 0; jj < 16; jj++) {
        const int nk = FILL_KV0 + 2 * jj;
        const uint32_t kcur = dslots + slot_k * SLOT16, vaddr = kcur + SLOT16;
        slot_k = (slot_k == NSLOT - 2) ? 0 : slot_k + 2;
        const uint32_t knext = dslots + slot_k * SLOT16;
        const bool first = (jj & 7) == 0;
        if (jj == 1) TSTAMP(8); if (jj == 8) TSTAMP(10); if (jj == 10) TSTAMP(12); if (jj == 15) TSTAMP(14);
        named_bar(4 + wg, 256);
        WG_FENCE();
        issue_pv(Ob, P, vprev, (jj & 7) != 1);
        WG_COMMIT();
        issue_s(Sb, dq + (jj >= 8 ? 4 * BLK16 : 0) + 512, kcur);
        WG_COMMIT();
        named_arrive(4 + (wg ^ 1), 256);
        if (jj == 8) finish_rows(sa);
        WG_WAIT(1);
        pin(Oa); pin(Sa);
        if (__builtin_expect(jj == 8 || suba, 0)) {
          if (jj == 8) {
            store_o_tile(qblk, 0, Oa, sa);
            sa.m0 = sa.m1 = sa.l0 = sa.l1 = 0.f; suba = false;
          } else {
            sub_ref(Sa, sa);
          }
        }
        softmax_tile(Sa, Oa, P, sa, suba, first);
        mbar_wait(bar_full + (nk + 1) * 8);
        WG_WAIT(0);
        release_kv(nk);
        named_bar(4 + wg, 256);
        WG_FENCE();
        issue_pv(Oa, P, vaddr, !first);
        WG_COMMIT();
        issue_s(Sa, dq + (jj >= 7 ? 4 * BLK16 : 0), knext);
        WG_COMMIT();
        named_arrive(4 + (wg ^ 1), 256);
        if (jj == 8) finish_rows(sbt);
        WG_WAIT(1);
        pin(Ob); pin(Sb);
        if (wi < 3) {
          if (__builtin_expect(jj == 8 || subb, 0)) {
            if (jj == 8) {
              store_o_tile(qblk, 64, Ob, sbt);
              sbt.m0 = sbt.m1 = sbt.l0 = sbt.l1 = 0.f; subb = false;
            } else {
              sub_ref(Sb, sbt);
            }
          }
          softmax_tile(Sb, Ob, P, sbt, subb, first);
        }
        WG_WAIT(0);
        vprev = vaddr;
      }
      if (wg == 0) named_bar(4, 256);
      WG_FENCE();
      issue_pv(Ob, P, vprev, 1); WG_COMMIT();
      pin(Oa);
      finish_rows(sa); finish_rows(sbt);
      store_o_tile(qblk + 4 * BLK, 0, Oa, sa);
      WG_WAIT(0);
      pin(Ob);
      release_kv(FILL_O0 - 1);
      if (wi < 3) store_o_tile(qblk + 4 * BLK, 64, Ob, sbt);
      fence_async_smem();
      TSTAMP(4);
      if (wg == 1) named_arrive(1, 256);
      named_bar(2 + wg, 128);
    }
    TSTAMP(5);
    {
      const int t128 = tid & 127;
      const uint4* pbase = g_part + (size_t)((b * 8 + j) * 8) * (8 * 128) + t128;
      const uint32_t xch = slots + (98 % NSLOT) * SLOT_BYTES + t128 * 16;
      float sum[56];
      uint4 v[8], v2[8];
      uint32_t tagbits = 0;
#pragma unroll
      for (int i = 0; i < 8; i++) v[i] = v2[i] = make_uint4(0, 0, 0, 0);
#pragma unroll
      for (int i = 0; i < 56; i++) sum[i] = 0.f;
#pragma unroll
      for (int si = 0; si < 5; si++) {
        const int s = 2 * si + (wg & 1);
        if (s > 8) break;
        const int ksplit = (si == 0 || si == 4) ? 2 : 4;
        float acc[56];
        if (s == 8) { add_partial(sum, v, pbase + ((j - 4) & 7) * (8 * 128), tagbits); pin(sum); }
        if (s > 0) named_bar(4 + wg, 256);
#pragma unroll
        for (int kh = 0; kh < 2; kh++) {
          if (kh == 1 && s == 0) named_bar(1, 256);
          if (kh == 1 && s == 8) load_chunks(v, pbase + ((j - 7) & 7) * (8 * 128), 128);
#pragma unroll 1
          for (int kq = (kh ? ksplit : 0); kq < (kh ? 4 : ksplit); kq++) {
            const int n = FILL_O0 + s * 4 + kq;
            const uint64_t da = mkdesc(dslots + (n % NSLOT) * SLOT16), db = mkdesc(dsb + (2 * o_quarter(kq)) * BLK16);
            mbar_wait(bar_full + n * 8);
            WG_FENCE();
#pragma unroll
            for (int kk = 0; kk < 8; kk++)
              wgmma_n112_ta(acc, da + kk * 128, db + ((kk >> 2) * BLK16 + (kk & 3) * 2), kk | kq);
            WG_COMMIT();
            if (kq == 3 && s < 8) named_arrive(4 + (wg ^ 1), 256);
            if (kq > 0) { WG_WAIT(1); if (n - 1 < NFILL - NSLOT) release_both(n - 1); }
          }
        }
        if (s < 2) {
          mbar_wait(bar_tag);
          asm volatile("ld.shared.u32 %0, [%1];" : "=r"(tagbits) : "r"(s_tag) : "memory");
        }
        if (s >= 5 && s < 8) add_partial(sum, v, pbase + ((j + 4 - s) & 7) * (8 * 128), tagbits);
        if (s >= 3 && s < 8) load_chunks(v, pbase + ((j + 2 - s) & 7) * (8 * 128), 128);
        if (s == 7) load_chunks(v2, pbase + ((j - 6) & 7) * (8 * 128), 128);
        pin(sum);
        if (s == 8) {
          TSTAMP(15);
          named_bar(1, 256);
#pragma unroll
          for (int i = 0; i < 14; i++) {
            float4 t;
            asm volatile("ld.shared.v4.f32 {%0, %1, %2, %3}, [%4];" : "=f"(t.x), "=f"(t.y), "=f"(t.z), "=f"(t.w) : "r"(xch + i * 2048) : "memory");
            sum[4 * i] += t.x; sum[4 * i + 1] += t.y; sum[4 * i + 2] += t.z; sum[4 * i + 3] += t.w;
          }
          add_partial(sum, v, pbase + ((j - 7) & 7) * (8 * 128), tagbits);
          WG_WAIT(0);
          pin(acc);
#pragma unroll
          for (int i = 0; i < 56; i++) sum[i] += acc[i];
          uint32_t pk[28];
          pack_tile(pk, sum);
          const uint32_t stg = slots + (100 % NSLOT) * SLOT_BYTES;
          store_tile_t(stg, pk, wi, lane);
          named_bar(2, 128);
          uint4* orow = reinterpret_cast<uint4*>(gout + (size_t)(b * SQ + (t128 >> 3)) * DM + j * 64) + (t128 & 7);
          const uint32_t src = stg + (t128 >> 3) * 128 + (((t128 & 7) ^ ((t128 >> 3) & 7)) << 4);
#pragma unroll
          for (int i = 0; i < 7; i++) {
            uint4 t;
            asm volatile("ld.shared.v4.u32 {%0, %1, %2, %3}, [%4];" : "=r"(t.x), "=r"(t.y), "=r"(t.z), "=r"(t.w) : "r"(src + i * 2048) : "memory");
            orow[(size_t)i * 16 * (DM / 8)] = t;
          }
          if (j == 0 && t128 == 0) atomicAdd(g_epoch + b, 1u);
        } else {
          WG_WAIT(0);
          TSTAMP(7 + (s >> 1) * 2);
          pin(acc);
          if (FILL_O0 + s * 4 + 3 < NFILL - NSLOT) release_both(FILL_O0 + s * 4 + 3);
          const float tagf = __uint_as_float(tagbits);
          if (s < 7) {
            uint4* dst = g_part + (size_t)((b * 8 + o_tile_of_step(j, s)) * 8 + j) * (8 * 128) + t128;
#pragma unroll
            for (int i = 0; i < 8; i++) store_chunk(dst + i * 128, acc + 7 * i, tagf);
          } else {
            uint4* dst = g_part8 + (size_t)(((b * 8 + 2 * wi) * 8 + j) * 4) * 32 + lane;
#pragma unroll
            for (int h = 0; h < 2; h++) {
              float e[28];
#pragma unroll
              for (int i = 0; i < 28; i++) e[i] = acc[4 * (i >> 1) + 2 * h + (i & 1)];
#pragma unroll
              for (int c = 0; c < 4; c++) store_chunk(dst + (h * 8 * 4 + c) * 32, e + 7 * c, tagf);
            }
          }
        }
      }
      if (wg == 1) {
        const uint4* s8 = g_part8 + (size_t)(((b * 8 + j) * 8) * 4 + wi) * 32 + lane;
        add_partial(sum, v, pbase + ((j - 5) & 7) * (8 * 128), tagbits);
        add_partial(sum, v2, pbase + ((j - 6) & 7) * (8 * 128), tagbits);
        named_bar(3, 128);
#pragma unroll
        for (int i = 0; i < 14; i++)
          asm volatile("st.shared.v4.f32 [%0], {%1, %2, %3, %4};" ::"r"(xch + i * 2048), "f"(sum[4 * i]), "f"(sum[4 * i + 1]), "f"(sum[4 * i + 2]), "f"(sum[4 * i + 3]) : "memory");
        named_arrive(1, 256);
        load_chunks(v, s8, 4 * 32);
        check_chunks(v, s8, 4 * 32, tagbits);
        float r[7];
#pragma unroll
        for (int i = 0; i < 7; i++) r[i] = 0.f;
#pragma unroll
        for (int d = 0; d < 8; d++) add_chunk(r, v[d]);
        const int odd = wi & 1;
        __nv_bfloat16* dst = gout + (size_t)(b * SQ + 4 * (7 * wi - odd) + 2 * (lane & 3)) * DM + 512 + 8 * j + (lane >> 2);
        __nv_bfloat16* dA = dst + odd * DM;
        __nv_bfloat16* dB = dst + (1 + 7 * odd) * DM;
#pragma unroll
        for (int i = 0; i < 7; i++) ((i & 1) ? dB : dA)[(i >> 1) * 8 * DM] = __float2bfloat16(r[i]);
      }
    }
    TSTAMP(6);
  }
}

typedef CUresult (*EncodeFn)(CUtensorMap*, CUtensorMapDataType, cuuint32_t, void*, const cuuint64_t*, const cuuint64_t*,
                             const cuuint32_t*, const cuuint32_t*, CUtensorMapInterleave, CUtensorMapSwizzle,
                             CUtensorMapL2promotion, CUtensorMapFloatOOBfill);

void make_map(EncodeFn enc, CUtensorMap* m, const void* ptr, int rank, const cuuint64_t* dims, const cuuint64_t* strides,
              const cuuint32_t* box) {
  cuuint32_t es[3] = {1, 1, 1};
  enc(m, CU_TENSOR_MAP_DATA_TYPE_BFLOAT16, rank, const_cast<void*>(ptr), dims, strides, box, es, CU_TENSOR_MAP_INTERLEAVE_NONE,
      CU_TENSOR_MAP_SWIZZLE_128B, CU_TENSOR_MAP_L2_PROMOTION_L2_128B, CU_TENSOR_MAP_FLOAT_OOB_FILL_NONE);
}

}

extern "C" void kernel_launch(void* const* d_in, const int* in_sizes, int n_in, void* d_out, int out_size) {
  (void)in_sizes; (void)n_in; (void)out_size;
  static EncodeFn enc = nullptr;
  if (!enc) {
    void* fn = nullptr;
    cudaDriverEntryPointQueryResult qr;
    cudaGetDriverEntryPoint("cuTensorMapEncodeTiled", &fn, cudaEnableDefault, &qr);
    enc = (EncodeFn)fn;
    cudaFuncSetAttribute(gqa_fused_kernel, cudaFuncAttributeMaxDynamicSharedMemorySize, SMEM_BYTES);
  }
  CUtensorMap tx, tk, tv, twq, two;
  {
    cuuint64_t d[2] = {DM, B_ * SQ}, s[1] = {DM * 2}; cuuint32_t bx[2] = {64, SQ};
    make_map(enc, &tx, d_in[0], 2, d, s, bx);
  }
  {
    cuuint64_t d[3] = {64, (cuuint64_t)B_ * HKV * SK, 2}, s[2] = {DH * 2, 128}; cuuint32_t bx[3] = {64, 64, 2};
    make_map(enc, &tk, d_in[1], 3, d, s, bx);
    make_map(enc, &tv, d_in[2], 3, d, s, bx);
  }
  {
    cuuint64_t d[2] = {HQ * DH, DM}, s[1] = {HQ * DH * 2}; cuuint32_t bx[2] = {64, 64};
    make_map(enc, &twq, d_in[3], 2, d, s, bx);
  }
  {
    cuuint64_t d[2] = {DM, HQ * DH}, s[1] = {DM * 2}; cuuint32_t bx[2] = {64, 64};
    make_map(enc, &two, d_in[4], 2, d, s, bx);
  }
  gqa_fused_kernel<<<128, NTHREADS, SMEM_BYTES>>>(tx, tk, tv, twq, two, (const uint8_t*)d_in[0], (const uint8_t*)d_in[1], (const uint8_t*)d_in[2],
                                                   (const uint8_t*)d_in[3], (const uint8_t*)d_in[4], (__nv_bfloat16*)d_out);
}
```

```cpp
#include <cuda_runtime.h>
#include <cuda_bf16.h>
#include <cuda.h>
#include <stdint.h>

namespace {

constexpr int B_ = 16, SQ = 112, DM = 576, HQ = 32, HKV = 16, SK = 512, DH = 128;
constexpr int NSLOT = 6;
constexpr int SLOT_BYTES = 16384;
constexpr int BLK = 112 * 128;
constexpr int NFILL_Q = 36, NFILL_KV = 32, NFILL_O = 36;
constexpr int FILL_KV0 = NFILL_Q, FILL_O0 = NFILL_Q + NFILL_KV, NFILL = FILL_O0 + NFILL_O;
constexpr int OFF_SLOTS = 8 * BLK;
constexpr int OFF_STAGE = OFF_SLOTS + NSLOT * SLOT_BYTES;
constexpr int OFF_BARS = OFF_STAGE + BLK;
constexpr int NBARS = 2 * NFILL + 9 + 4 + 1;
constexpr int OFF_AUX = OFF_BARS + NBARS * 8 + 16;
constexpr int SMEM_BYTES = OFF_AUX + 4 * 112 * 4;
constexpr int NTHREADS = 384;
constexpr int PF_DIST = 12, PF_Q0 = 6, PF_QS = 5, PF_LAG = 4, PF_SPAN = 25;
constexpr int XH = 6;
constexpr uint32_t SPIN_LIMIT = 1u << 18;

__device__ uint4 g_part[B_ * 8 * 8 * 8 * 128];
__device__ uint4 g_part8[B_ * 8 * 8 * 4 * 32];
__device__ uint32_t g_epoch[B_];

__device__ __forceinline__ uint32_t smem_u32(const void* p) { return (uint32_t)__cvta_generic_to_shared(p); }
__device__ __forceinline__ void mbar_init(uint32_t bar, uint32_t cnt) { asm volatile("mbarrier.init.shared::cta.b64 [%0], %1;" ::"r"(bar), "r"(cnt) : "memory"); }
__device__ __forceinline__ void mbar_expect_tx(uint32_t bar, uint32_t bytes) { asm volatile("mbarrier.arrive.expect_tx.shared::cta.b64 _, [%0], %1;" ::"r"(bar), "r"(bytes) : "memory"); }
__device__ __forceinline__ void mbar_arrive_pred(uint32_t bar, bool p) { asm volatile("{\n.reg .pred p;\nsetp.ne.b32 p, %1, 0;\n@p mbarrier.arrive.shared::cta.b64 _, [%0];\n}\n" ::"r"(bar), "r"((int)p) : "memory"); }
__device__ __forceinline__ void mbar_arrive_remote_pred(uint32_t rbar, bool p) { asm volatile("{\n.reg .pred p;\nsetp.ne.b32 p, %1, 0;\n@p mbarrier.arrive.shared::cluster.b64 _, [%0];\n}\n" ::"r"(rbar), "r"((int)p) : "memory"); }
__device__ __forceinline__ void mbar_wait_sleep(uint32_t bar) {
  uint32_t done, it = 0;
  do {
    asm volatile("{\n.reg .pred p;\nmbarrier.try_wait.parity.shared::cta.b64 p, [%1], 0, %2;\nselp.u32 %0, 1, 0, p;\n}\n" : "=r"(done) : "r"(bar), "r"(100000u) : "memory");
    if (++it > 4096) break;
  } while (!done);
}
__device__ __forceinline__ void mbar_wait(uint32_t bar) {
  asm volatile("{\n.reg .pred p;\n.reg .u32 c;\n"
               "mbarrier.try_wait.parity.shared::cta.b64 p, [%0], 0;\n@p bra.uni DONE;\nmov.u32 c, 0;\n"
               "LOOP:\nmbarrier.try_wait.parity.shared::cta.b64 p, [%0], 0;\n@p bra.uni DONE;\n"
               "add.u32 c, c, 1;\nsetp.lt.u32 p, c, %1;\n@p bra.uni LOOP;\nDONE:\n}\n" ::"r"(bar), "n"(SPIN_LIMIT) : "memory");
}
__device__ __forceinline__ uint32_t mapa(uint32_t addr, uint32_t cta) { uint32_t r; asm volatile("mapa.shared::cluster.u32 %0, %1, %2;" : "=r"(r) : "r"(addr), "r"(cta)); return r; }
__device__ __forceinline__ void tma_2d(uint32_t dst, const CUtensorMap* m, int c0, int c1, uint32_t bar) {
  asm volatile("cp.async.bulk.tensor.2d.shared::cluster.global.mbarrier::complete_tx::bytes [%0], [%1, {%3, %4}], [%2];" ::"r"(dst), "l"(m), "r"(bar), "r"(c0), "r"(c1) : "memory");
}
__device__ __forceinline__ void tma_2d_mc(uint32_t dst, const CUtensorMap* m, int c0, int c1, uint32_t bar) {
  asm volatile("cp.async.bulk.tensor.2d.shared::cluster.global.mbarrier::complete_tx::bytes.multicast::cluster [%0], [%1, {%3, %4}], [%2], %5;" ::"r"(dst), "l"(m), "r"(bar), "r"(c0), "r"(c1), "h"((uint16_t)3) : "memory");
}
__device__ __forceinline__ void tma_3d(uint32_t dst, const CUtensorMap* m, int c0, int c1, int c2, uint32_t bar, uint64_t pol) {
  asm volatile("cp.async.bulk.tensor.3d.shared::cluster.global.mbarrier::complete_tx::bytes.L2::cache_hint [%0], [%1, {%3, %4, %5}], [%2], %6;" ::"r"(dst), "l"(m), "r"(bar), "r"(c0), "r"(c1), "r"(c2), "l"(pol) : "memory");
}
__device__ __forceinline__ uint4 ld_relaxed_b128(const uint4* p) {
  uint4 v;
  asm volatile("{\n.reg .b64 l, h;\n.reg .b128 t;\nld.relaxed.gpu.global.b128 t, [%4];\nmov.b128 {l, h}, t;\n"
               "mov.b64 {%0, %1}, l;\nmov.b64 {%2, %3}, h;\n}\n" : "=r"(v.x), "=r"(v.y), "=r"(v.z), "=r"(v.w) : "l"(p) : "memory");
  return v;
}
__device__ __forceinline__ void l2_prefetch(const void* p, uint32_t bytes) { asm volatile("cp.async.bulk.prefetch.L2.global [%0], %1;" ::"l"(p), "r"(bytes) : "memory"); }
__device__ __forceinline__ void prefetch_line(const void* p) { asm volatile("prefetch.global.L2 [%0];" ::"l"(p)); }
__device__ __forceinline__ void prefetch_tmap(const CUtensorMap* m) { asm volatile("prefetch.tensormap [%0];" ::"l"(m) : "memory"); }
__device__ __forceinline__ bool elect_one() { uint32_t p; asm volatile("{\n.reg .pred p;\nelect.sync _|p, 0xffffffff;\nselp.u32 %0, 1, 0, p;\n}\n" : "=r"(p)); return p != 0; }
__device__ __forceinline__ void named_bar(int id, int n) { asm volatile("bar.sync %0, %1;" ::"r"(id), "r"(n) : "memory"); }
__device__ __forceinline__ void named_arrive(int id, int n) { asm volatile("bar.arrive %0, %1;" ::"r"(id), "r"(n) : "memory"); }
__device__ __forceinline__ void sts64(uint32_t a, float x, float y) { asm volatile("st.shared.v2.f32 [%0], {%1, %2};" ::"r"(a), "f"(x), "f"(y) : "memory"); }
__device__ __forceinline__ void sts32(uint32_t a, float x) { asm volatile("st.shared.f32 [%0], %1;" ::"r"(a), "f"(x) : "memory"); }
__device__ __forceinline__ float2 lds64(uint32_t a) { float2 v; asm volatile("ld.shared.v2.f32 {%0, %1}, [%2];" : "=f"(v.x), "=f"(v.y) : "r"(a) : "memory"); return v; }
__device__ __forceinline__ float4 lds128(uint32_t a) { float4 v; asm volatile("ld.shared.v4.f32 {%0, %1, %2, %3}, [%4];" : "=f"(v.x), "=f"(v.y), "=f"(v.z), "=f"(v.w) : "r"(a) : "memory"); return v; }
__device__ __forceinline__ float lds32(uint32_t a) { float v; asm volatile("ld.shared.f32 %0, [%1];" : "=f"(v) : "r"(a) : "memory"); return v; }
__device__ __forceinline__ int opaque_tid() { int t; asm volatile("mov.u32 %0, %%tid.x;" : "=r"(t)); return t; }
__device__ __forceinline__ void sched_fence(int zero) { asm volatile("{\n.reg .pred p;\nsetp.ne.b32 p, %0, 0;\nL:\n@p nanosleep.u32 1;\n@p bra.uni L;\n}\n" ::"r"(zero) : "memory"); }
__device__ __forceinline__ void fence_async_smem() { asm volatile("fence.proxy.async.shared::cta;" ::: "memory"); }
#define WG_FENCE() asm volatile("wgmma.fence.sync.aligned;" ::: "memory")
#define WG_COMMIT() asm volatile("wgmma.commit_group.sync.aligned;" ::: "memory")
#define WG_WAIT(n) asm volatile("wgmma.wait_group.sync.aligned %0;" ::"n"(n) : "memory")
template <int N> __device__ __forceinline__ void pin(float (&d)[N]) {
#pragma unroll
  for (int i = 0; i < N; i++) asm volatile("" : "+f"(d[i])::"memory");
}
__device__ __forceinline__ uint64_t mkdesc(uint32_t lo) { return ((uint64_t)(64u | (1u << 30)) << 32) | lo; }
__device__ __forceinline__ uint32_t pack_bf16(float lo, float hi) { uint32_t r; asm("cvt.rn.bf16x2.f32 %0, %1, %2;" : "=r"(r) : "f"(hi), "f"(lo)); return r; }
__device__ __forceinline__ float ex2(float x) { float r; asm("ex2.approx.ftz.f32 %0, %1;" : "=f"(r) : "f"(x)); return r; }
__device__ __forceinline__ float rcp_fast(float x) { float r; asm("rcp.approx.ftz.f32 %0, %1;" : "=f"(r) : "f"(x)); return r; }
__device__ __forceinline__ void stsm_x4_t(uint32_t addr, uint32_t r0, uint32_t r1, uint32_t r2, uint32_t r3) {
  asm volatile("stmatrix.sync.aligned.m8n8.x4.trans.shared.b16 [%0], {%1, %2, %3, %4};" ::"r"(addr), "r"(r0), "r"(r1), "r"(r2), "r"(r3) : "memory");
}

__device__ __forceinline__ void wgmma_n112_ta(float (&d)[56], uint64_t da, uint64_t db, int sc) {
  asm volatile("{\n.reg .pred p;\nsetp.ne.b32 p, %58, 0;\n"
    "wgmma.mma_async.sync.aligned.m64n112k16.f32.bf16.bf16 "
    "{%0, %1, %2, %3, %4, %5, %6, %7, %8, %9, %10, %11, %12, %13, %14, %15, %16, %17, %18, %19, %20, %21, %22, %23, %24, %25, %26, %27, %28, %29, %30, %31, %32, %33, %34, %35, %36, %37, %38, %39, %40, %41, %42, %43, %44, %45, %46, %47, %48, %49, %50, %51, %52, %53, %54, %55}, "
    "%56, %57, p, 1, 1, 1, 0;\n}\n"
    : "+f"(d[0]), "+f"(d[1]), "+f"(d[2]), "+f"(d[3]), "+f"(d[4]), "+f"(d[5]), "+f"(d[6]), "+f"(d[7]), "+f"(d[8]), "+f"(d[9]), "+f"(d[10]), "+f"(d[11]), "+f"(d[12]), "+f"(d[13]), "+f"(d[14]), "+f"(d[15]), "+f"(d[16]), "+f"(d[17]), "+f"(d[18]), "+f"(d[19]), "+f"(d[20]), "+f"(d[21]), "+f"(d[22]), "+f"(d[23]), "+f"(d[24]), "+f"(d[25]), "+f"(d[26]), "+f"(d[27]), "+f"(d[28]), "+f"(d[29]), "+f"(d[30]), "+f"(d[31]), "+f"(d[32]), "+f"(d[33]), "+f"(d[34]), "+f"(d[35]), "+f"(d[36]), "+f"(d[37]), "+f"(d[38]), "+f"(d[39]), "+f"(d[40]), "+f"(d[41]), "+f"(d[42]), "+f"(d[43]), "+f"(d[44]), "+f"(d[45]), "+f"(d[46]), "+f"(d[47]), "+f"(d[48]), "+f"(d[49]), "+f"(d[50]), "+f"(d[51]), "+f"(d[52]), "+f"(d[53]), "+f"(d[54]), "+f"(d[55])
    : "l"(da), "l"(db), "r"(sc));
}

__device__ __forceinline__ void wgmma_n112_kk(float (&d)[56], uint64_t da, uint64_t db, int sc) {
  asm volatile("{\n.reg .pred p;\nsetp.ne.b32 p, %58, 0;\n"
    "wgmma.mma_async.sync.aligned.m64n112k16.f32.bf16.bf16 "
    "{%0, %1, %2, %3, %4, %5, %6, %7, %8, %9, %10, %11, %12, %13, %14, %15, %16, %17, %18, %19, %20, %21, %22, %23, %24, %25, %26, %27, %28, %29, %30, %31, %32, %33, %34, %35, %36, %37, %38, %39, %40, %41, %42, %43, %44, %45, %46, %47, %48, %49, %50, %51, %52, %53, %54, %55}, "
    "%56, %57, p, 1, 1, 0, 0;\n}\n"
    : "+f"(d[0]), "+f"(d[1]), "+f"(d[2]), "+f"(d[3]), "+f"(d[4]), "+f"(d[5]), "+f"(d[6]), "+f"(d[7]), "+f"(d[8]), "+f"(d[9]), "+f"(d[10]), "+f"(d[11]), "+f"(d[12]), "+f"(d[13]), "+f"(d[14]), "+f"(d[15]), "+f"(d[16]), "+f"(d[17]), "+f"(d[18]), "+f"(d[19]), "+f"(d[20]), "+f"(d[21]), "+f"(d[22]), "+f"(d[23]), "+f"(d[24]), "+f"(d[25]), "+f"(d[26]), "+f"(d[27]), "+f"(d[28]), "+f"(d[29]), "+f"(d[30]), "+f"(d[31]), "+f"(d[32]), "+f"(d[33]), "+f"(d[34]), "+f"(d[35]), "+f"(d[36]), "+f"(d[37]), "+f"(d[38]), "+f"(d[39]), "+f"(d[40]), "+f"(d[41]), "+f"(d[42]), "+f"(d[43]), "+f"(d[44]), "+f"(d[45]), "+f"(d[46]), "+f"(d[47]), "+f"(d[48]), "+f"(d[49]), "+f"(d[50]), "+f"(d[51]), "+f"(d[52]), "+f"(d[53]), "+f"(d[54]), "+f"(d[55])
    : "l"(da), "l"(db), "r"(sc));
}


__device__ __forceinline__ uint32_t stsm_t_base(uint32_t blk, int wi, int lane) {
  const int mi = lane >> 3, r = lane & 7;
  return blk + (uint32_t)(((mi >> 1) * 8 + r) * 128 + (((2 * wi + (mi & 1)) ^ r) << 4));
}
template <int I0, int I1>
__device__ __forceinline__ void store_tile_at(uint32_t base, const uint32_t (&pk)[28]) {
#pragma unroll
  for (int i = I0; i < I1; i++) stsm_x4_t(base + i * 2048, pk[4 * i], pk[4 * i + 1], pk[4 * i + 2], pk[4 * i + 3]);
}
template <int I0 = 0, int I1 = 7>
__device__ __forceinline__ void store_tile_t(uint32_t blk, const uint32_t (&pk)[28], int wi, int lane) {
  store_tile_at<I0, I1>(stsm_t_base(blk, wi, lane), pk);
}
__device__ __forceinline__ void pack_tile(uint32_t (&pk)[28], const float (&a)[56]) {
#pragma unroll
  for (int i = 0; i < 28; i++) pk[i] = pack_bf16(a[2 * i], a[2 * i + 1]);
}

constexpr float SCALE_LOG2E = 0.08838834764831845f * 1.4426950408889634f;
__device__ __forceinline__ void pack_tile_scaled(uint32_t (&pk)[28], const float (&a)[56]) {
#pragma unroll
  for (int i = 0; i < 28; i++) pk[i] = pack_bf16(a[2 * i] * SCALE_LOG2E, a[2 * i + 1] * SCALE_LOG2E);
}

constexpr int L_HI_BITS = 0x4B800000;
constexpr float T_LO = -24.0f;
template <int I0, int I1>
__device__ __forceinline__ void exp_groups(const float (&T)[56], uint32_t (&pk)[28], float (&l)[28], float keep, int& mx) {
#pragma unroll
  for (int i = I0; i < I1; i++) {
    const float p0 = ex2(T[4 * i]), p1 = ex2(T[4 * i + 1]), p2 = ex2(T[4 * i + 2]), p3 = ex2(T[4 * i + 3]);
    l[2 * i] = fmaf(l[2 * i], keep, p0 + p2); l[2 * i + 1] = fmaf(l[2 * i + 1], keep, p1 + p3);
    pk[2 * i] = pack_bf16(p0, p1); pk[2 * i + 1] = pack_bf16(p2, p3);
    mx = __vimax3_s32(mx, __float_as_int(l[2 * i]), __float_as_int(l[2 * i + 1]));
  }
}
__device__ __forceinline__ void spill_sums(const float (&l)[28], uint32_t o) {
#pragma unroll
  for (int i = 0; i < 14; i++) sts64(o + i * 32, l[2 * i], l[2 * i + 1]);
}
__device__ __forceinline__ void sum_columns(const float (&l)[28], uint32_t scratch, uint32_t aux, int bar) {
  const int t128 = threadIdx.x & 127;
  spill_sums(l, scratch + (t128 >> 2) * 480 + (t128 & 3) * 8);
  named_bar(bar, 128);
  const int t = min(t128, 111 - 3 + (t128 & 3));
  const uint32_t rd = scratch + (t & 3) * 480 + (t >> 2) * 16;
  float4 a = lds128(rd);
#pragma unroll
  for (int r = 1; r < 8; r++) { const float4 x = lds128(rd + r * 4 * 480); a.x += x.x; a.y += x.y; a.z += x.z; a.w += x.w; }
  const bool h1 = t & 2, h0 = t & 1;
  const float u = (h1 ? a.z : a.x) + __shfl_xor_sync(0xffffffffu, h1 ? a.x : a.z, 2);
  const float v = (h1 ? a.w : a.y) + __shfl_xor_sync(0xffffffffu, h1 ? a.y : a.w, 2);
  sts32(aux + 448 + t * 4, rcp_fast((h0 ? v : u) + __shfl_xor_sync(0xffffffffu, h0 ? u : v, 1)));
}
__device__ __forceinline__ void store_o(uint32_t base, const float (&O0)[56], const float (&O1)[56], float (&l)[28], uint32_t inv) {
#pragma unroll
  for (int i = 0; i < 14; i++) { const float2 u = lds64(inv + i * 32); l[2 * i] = u.x; l[2 * i + 1] = u.y; }
#pragma unroll
  for (int i = 0; i < 14; i += 2) {
    const float ux = l[2 * i], uy = l[2 * i + 1], wx = l[2 * i + 2], wy = l[2 * i + 3];
    stsm_x4_t(base + i * 1024, pack_bf16(O0[4 * i] * ux, O0[4 * i + 1] * uy), pack_bf16(O0[4 * i + 2] * ux, O0[4 * i + 3] * uy),
              pack_bf16(O0[4 * i + 4] * wx, O0[4 * i + 5] * wy), pack_bf16(O0[4 * i + 6] * wx, O0[4 * i + 7] * wy));
    stsm_x4_t(base + BLK + i * 1024, pack_bf16(O1[4 * i] * ux, O1[4 * i + 1] * uy), pack_bf16(O1[4 * i + 2] * ux, O1[4 * i + 3] * uy),
              pack_bf16(O1[4 * i + 4] * wx, O1[4 * i + 5] * wy), pack_bf16(O1[4 * i + 6] * wx, O1[4 * i + 7] * wy));
  }
}
__device__ __forceinline__ bool underflows(const float (&S)[56]) {
  uint32_t a = 0, c = 0;
#pragma unroll
  for (int i = 0; i < 14; i += 2) {
    a = __vimax3_u32(a, __float_as_uint(S[4 * i]), __float_as_uint(S[4 * i + 1]));
    c = __vimax3_u32(c, __float_as_uint(S[4 * i + 4]), __float_as_uint(S[4 * i + 5]));
  }
  return max(a, c) > __float_as_uint(T_LO);
}
__device__ __forceinline__ void sub_ref(float (&T)[56], uint32_t aux, int zero) {
  const uint32_t a = aux + (opaque_tid() & 3) * 8;
#pragma unroll
  for (int i = 0; i < 14; i++) {
    const float2 m = lds64(a + i * 32);
    T[4 * i] -= m.x; T[4 * i + 1] -= m.y; T[4 * i + 2] -= m.x; T[4 * i + 3] -= m.y;
    if (i == 4 || i == 9) sched_fence(zero);
  }
}
__device__ __forceinline__ void redo_block(float (&T)[56], float (&O0)[56], float (&O1)[56], float (&l)[28], const uint8_t* kblk,
                                           uint32_t q16, uint32_t pbuf, uint32_t aux, int bar, bool first, bool sub, int zero) {
  const int t128 = opaque_tid() & 127, lane = t128 & 31, wi = t128 >> 5;
  const uint32_t o = pbuf + (t128 >> 2) * 448 + (t128 & 3) * 8;
#pragma unroll
  for (int h = 0; h < 2; h++) {
#pragma unroll 1
    for (int i = 0; i < 4; i++) {
      const int row = i * 16 + (t128 >> 3), c = t128 & 7;
      const uint4 v = *reinterpret_cast<const uint4*>(kblk + row * 256 + h * 128 + c * 16);
      asm volatile("st.shared.v4.b32 [%0], {%1, %2, %3, %4};" ::"r"(pbuf + row * 128 + ((c ^ (row & 7)) << 4)), "r"(v.x), "r"(v.y), "r"(v.z), "r"(v.w) : "memory");
    }
    fence_async_smem();
    named_bar(bar, 128);
    WG_FENCE();
    const uint64_t dk = mkdesc((pbuf & 0x3FFFF) >> 4), dq = mkdesc(q16 + h * (BLK / 16));
#pragma unroll
    for (int kk = 0; kk < 4; kk++) wgmma_n112_kk(T, dk + kk * 2, dq + kk * 2, (h | kk) != 0);
    WG_COMMIT();
    WG_WAIT(0);
    pin(T);
    named_bar(bar, 128);
  }
  if (sub) sub_ref(T, aux, zero);
#pragma unroll
  for (int i = 0; i < 14; i++) sts64(o + i * 32, fmaxf(T[4 * i], T[4 * i + 2]), fmaxf(T[4 * i + 1], T[4 * i + 3]));
  named_bar(bar, 128);
  {
    const int c = min(t128, 111);
    float d = lds32(pbuf + c * 4);
#pragma unroll 1
    for (int r = 1; r < 32; r++) d = fmaxf(d, lds32(pbuf + r * 448 + c * 4));
    if (!first) d = fmaxf(d, 0.f);
    const float old = lds32(aux + c * 4);
    __syncwarp();
    sts32(aux + 448 + c * 4, d);
    sts32(aux + c * 4, sub ? old + d : d);
  }
  named_bar(bar, 128);
  const uint32_t base = stsm_t_base(pbuf, wi, lane);
#pragma unroll
  for (int i2 = 0; i2 < 7; i2++) {
    uint32_t pk[4];
#pragma unroll
    for (int i = 2 * i2; i < 2 * i2 + 2; i++) {
      const float2 d = lds64(aux + 448 + (lane & 3) * 8 + i * 32);
      const float r0 = ex2(-d.x), r1 = ex2(-d.y);
      const float p0 = ex2(T[4 * i] - d.x), p1 = ex2(T[4 * i + 1] - d.y), p2 = ex2(T[4 * i + 2] - d.x), p3 = ex2(T[4 * i + 3] - d.y);
      l[2 * i] = (!first && l[2 * i] < 0x1p100f) ? l[2 * i] * r0 : p0 + p2;
      l[2 * i + 1] = (!first && l[2 * i + 1] < 0x1p100f) ? l[2 * i + 1] * r1 : p1 + p3;
      pk[2 * (i & 1)] = pack_bf16(p0, p1); pk[2 * (i & 1) + 1] = pack_bf16(p2, p3);
      O0[4 * i] *= r0; O0[4 * i + 1] *= r1; O0[4 * i + 2] *= r0; O0[4 * i + 3] *= r1;
      O1[4 * i] *= r0; O1[4 * i + 1] *= r1; O1[4 * i + 2] *= r0; O1[4 * i + 3] *= r1;
    }
    stsm_x4_t(base + i2 * 2048, pk[0], pk[1], pk[2], pk[3]);
    sched_fence(zero);
  }
  fence_async_smem();
  named_bar(bar, 128);
}
__device__ __forceinline__ void issue_s(float (&S)[56], uint32_t k16, uint32_t q16) {
  const uint64_t dk = mkdesc(k16), dq = mkdesc(q16);
#pragma unroll
  for (int kk = 0; kk < 8; kk++)
    wgmma_n112_kk(S, dk + ((kk >> 2) * 512 + (kk & 3) * 2), dq + ((kk >> 2) * (BLK / 16) + (kk & 3) * 2), kk != 0);
}
__device__ __forceinline__ void issue_pv(float (&O0)[56], float (&O1)[56], uint32_t v16, uint32_t p16, int acc) {
  const uint64_t dv = mkdesc(v16), dp = mkdesc(p16);
#pragma unroll
  for (int kk = 0; kk < 4; kk++) {
    wgmma_n112_ta(O0, dv + kk * 128, dp + kk * 2, kk ? 1 : acc);
    wgmma_n112_ta(O1, dv + (512 + kk * 128), dp + kk * 2, kk ? 1 : acc);
  }
}
__device__ __forceinline__ int kv_next(int slot) { return slot == 3 ? 5 : (slot == 5 ? 0 : slot + 1); }
__device__ __forceinline__ bool kv_is_k(int c) { return c == 0 || ((c & 1) && c < 31); }
__device__ __forceinline__ int kv_block(int c) { return c == 31 ? 15 : ((c & 1) ? (c + 1) >> 1 : (c >> 1) - (c > 0)); }
__host__ __device__ constexpr int wo_slot(int i6) { return (0x140532 >> (4 * i6)) & 7; }

__device__ __forceinline__ int o_tile_of_step(int j, int s) { return s == 7 ? 8 : ((j + 1 + s - (s == 8)) & 7); }
__device__ __forceinline__ int o_quarter(int kq) { return ((kq & 1) << 1) | (kq >> 1); }

__device__ __forceinline__ void store_chunk(uint4* p, const float* a, float tagf) {
  asm volatile("st.relaxed.gpu.global.v4.b32 [%0], {%1, %2, %3, %4};" ::"l"(p), "r"(pack_bf16(a[0], a[1])),
               "r"(pack_bf16(a[2], a[3])), "r"(pack_bf16(a[4], a[5])), "r"(pack_bf16(a[6], tagf)) : "memory");
}
__device__ __forceinline__ void add_chunk(float* a, const uint4& v) {
  a[0] += __uint_as_float(v.x << 16); a[1] += __uint_as_float(v.x & 0xffff0000u);
  a[2] += __uint_as_float(v.y << 16); a[3] += __uint_as_float(v.y & 0xffff0000u);
  a[4] += __uint_as_float(v.z << 16); a[5] += __uint_as_float(v.z & 0xffff0000u);
  a[6] += __uint_as_float(v.w << 16);
}
__device__ __forceinline__ void load_chunks(uint4 (&v)[8], const uint4* p, int stride) {
#pragma unroll
  for (int i = 0; i < 8; i++) v[i] = ld_relaxed_b128(p + i * stride);
}
__device__ __forceinline__ void check_chunks(uint4 (&v)[8], const uint4* p, int stride, uint32_t tagbits) {
  uint32_t it = 0;
  for (;;) {
    uint32_t bad = 0;
#pragma unroll
    for (int i = 0; i < 8; i++) bad |= v[i].w ^ tagbits;
    if (!__any_sync(0xffffffffu, bad > 0xffffu) || ++it > SPIN_LIMIT) break;
    load_chunks(v, p, stride);
  }
}
__device__ __forceinline__ void add_partial(float (&a)[56], uint4 (&v)[8], const uint4* p, uint32_t tagbits) {
  check_chunks(v, p, 128, tagbits);
#pragma unroll
  for (int i = 0; i < 8; i++) add_chunk(a + 7 * i, v[i]);
}

__host__ __device__ constexpr uint32_t bar_count(int i) {
  return (i == 2 * NFILL + 9 || i == 2 * NFILL + 11) ? 4
       : (i == 2 * NFILL + 10 || i == 2 * NFILL + 12) ? 2
       : i >= 2 * NFILL ? 1
       : i >= NFILL ? ((i - NFILL >= FILL_O0 - 5 && i - NFILL < FILL_O0) ? 16 : 8)
       : 1;
}
template <int W> __device__ __forceinline__ void init_barriers(uint32_t base, int w) {
  constexpr int NW = NTHREADS / 32 - 1, PER = (NBARS + NW - 1) / NW;
  if (w == W) {
#pragma unroll
    for (int i = W * PER; i < (W + 1) * PER && i < NBARS; i++)
      if (i > 1 && i != 2 * NFILL && i != 2 * NFILL + 1) mbar_init(base + i * 8, bar_count(i));
  } else if constexpr (W + 1 < NW) {
    init_barriers<W + 1>(base, w);
  }
}

__global__ void __cluster_dims__(2, 1, 1) __launch_bounds__(NTHREADS, 1)
gqa_fused_kernel(const __grid_constant__ CUtensorMap tm_x, const __grid_constant__ CUtensorMap tm_k,
                 const __grid_constant__ CUtensorMap tm_v, const __grid_constant__ CUtensorMap tm_wq,
                 const __grid_constant__ CUtensorMap tm_wo, const uint8_t* __restrict__ gx,
                 const uint8_t* __restrict__ gk, const uint8_t* __restrict__ gv, const uint8_t* __restrict__ gwq,
                 const uint8_t* __restrict__ gwo, __nv_bfloat16* __restrict__ gout, int zero) {
  extern __shared__ __align__(1024) uint8_t smem[];
  const uint32_t sb = smem_u32(smem);
  const uint32_t slots = sb + OFF_SLOTS;
  const uint32_t bar_full = sb + OFF_BARS, bar_empty = bar_full + NFILL * 8, bar_x = bar_empty + NFILL * 8, bar_sum = bar_x + 9 * 8, bar_tag = bar_sum + 4 * 8,
                 s_tag = bar_tag + 8, stage = sb + OFF_STAGE;
  const int tid = threadIdx.x, lane = tid & 31;
  const int wg = __shfl_sync(0xffffffffu, tid >> 7, 0), wi = __shfl_sync(0xffffffffu, (tid >> 5) & 3, 0);
  const uint32_t rank = blockIdx.x & 1;
  const int cl = blockIdx.x >> 1;
  const int j = cl & 7, b = (cl >> 3) * 2 + (int)rank;

  if (tid < 32) prefetch_line(gwq + (size_t)(64 + b * 8 + (tid >> 2)) * (HQ * DH * 2) + j * 1024 + (tid & 3) * 128);
  else if (tid < 60) prefetch_line(gx + (size_t)(b * SQ + j * 14 + ((tid - 32) >> 1)) * (DM * 2) + 256 + (tid & 1) * 128);
  if (tid == 256) {
    mbar_init(bar_full, 1); mbar_init(bar_full + 8, 1); mbar_init(bar_x, 1); mbar_init(bar_x + 8, 1);
    asm volatile("fence.mbarrier_init.release.cluster;" ::: "memory");
    fence_async_smem();
    mbar_expect_tx(bar_x, BLK);
    tma_2d(sb, &tm_x, 0, b * SQ, bar_x);
#pragma unroll
    for (int w = 0; w < 2; w++) {
      mbar_expect_tx(bar_full + w * 8, SLOT_BYTES);
      tma_2d(slots + w * SLOT_BYTES, &tm_wq, (4 * j + w) * DH, 0, bar_full + w * 8);
      tma_2d(slots + w * SLOT_BYTES + 8192, &tm_wq, (4 * j + w) * DH + 64, 0, bar_full + w * 8);
    }
    mbar_expect_tx(bar_x + 8, BLK);
    tma_2d(sb + BLK, &tm_x, 64, b * SQ, bar_x + 8);
  } else if (lane == 0) {
    init_barriers<0>(bar_full, wg * 4 + wi - (wg == 2));
    asm volatile("fence.mbarrier_init.release.cluster;" ::: "memory");
    if (tid == 288) { prefetch_tmap(&tm_k); prefetch_tmap(&tm_v); prefetch_tmap(&tm_wo); }
  }
  __syncwarp();
  __syncthreads();
  asm volatile("barrier.cluster.arrive.relaxed.aligned;" ::: "memory");
  __syncwarp();
  asm volatile("barrier.cluster.wait.acquire.aligned;" ::: "memory");

  if (wg == 2) {
    asm volatile("setmaxnreg.dec.sync.aligned.u32 40;");
    if (wi < 2) {
      const uint32_t slot0 = slots + wi * SLOT_BYTES;
      uint32_t dst = slot0, fb = bar_full + wi * 8;
      auto next = [&]() { dst = (dst == slot0 + 4 * SLOT_BYTES) ? slot0 : dst + 2 * SLOT_BYTES; fb += 16; };
      constexpr uint32_t EMPTY_OFF = NFILL * 8 - NSLOT * 8;
      int c0 = (4 * j + wi) * DH + (int)rank * 64;
      next();
#pragma unroll 1
      for (int t = 1; t < 18; t++) {
        const int k = t < 9 ? t : t - 9;
        if (t == 9) c0 += 2 * DH;
        if (t >= 3) mbar_wait_sleep(fb + EMPTY_OFF);
        if (elect_one()) {
          mbar_expect_tx(fb, SLOT_BYTES);
          tma_2d_mc(dst + rank * 8192, &tm_wq, c0, k * 64, fb);
          if (t < 8 && wi == 1) {
            mbar_expect_tx(bar_x + (t + 1) * 8, BLK);
            tma_2d(t < 7 ? sb + (t + 1) * BLK : stage, &tm_x, (t + 1) * 64, b * SQ, bar_x + (t + 1) * 8);
          }
        }
        next();
      }
#pragma unroll 1
      for (int g = 0; g < 2; g++) {
        int ln = opaque_tid() & 31;
        const uint32_t rd = sb + 2 * g * BLK + (ln & 1) * 480 + (14 * wi + min(ln >> 1, 13)) * 16;
        mbar_wait_sleep(bar_sum + g * 16);
        float4 a = lds128(rd);
#pragma unroll
        for (int r = 1; r < 16; r += 3) {
          const float4 x = lds128(rd + r * 960), y = lds128(rd + (r + 1) * 960), z = lds128(rd + (r + 2) * 960);
          a.x += x.x; a.y += x.y; a.z += x.z; a.w += x.w;
          a.x += y.x; a.y += y.y; a.z += y.z; a.w += y.w;
          a.x += z.x; a.y += z.y; a.z += z.z; a.w += z.w;
        }
        ln = opaque_tid() & 31;
        const bool h = ln & 1;
        const float u = (h ? a.z : a.x) + __shfl_xor_sync(0xffffffffu, h ? a.x : a.z, 1);
        const float v = (h ? a.w : a.y) + __shfl_xor_sync(0xffffffffu, h ? a.y : a.w, 1);
        sts64(sb + OFF_AUX + g * 896 + 448 + (14 * wi + min(ln >> 1, 13)) * 16 + (ln & 1) * 8, rcp_fast(u), rcp_fast(v));
        __syncwarp();
        mbar_arrive_pred(bar_sum + g * 16 + 8, ln == 0);
      }
      fb += 16 * 16;
      const int r0 = j * 512 + wi * 256 + (int)rank * 64;
      int i6 = wi;
#pragma unroll 1
      for (int t = 0; t < 18; t++) {
        mbar_wait_sleep(t > 2 ? fb + EMPTY_OFF : bar_empty + (t < 2 ? 63 + 2 * t + wi : (wi ? 67 : 34)) * 8);
        const int cw = o_tile_of_step(j, t >> 1) * 64;
        if (elect_one()) {
          mbar_expect_tx(fb, SLOT_BYTES);
          tma_2d_mc(slots + wo_slot(i6) * SLOT_BYTES + rank * 8192, &tm_wo, cw, r0 + (t & 1) * 128, fb);
        }
        fb += 16;
        i6 = i6 >= 4 ? i6 - 4 : i6 + 2;
      }
    } else if (wi == 2) {
      const size_t kv0 = (size_t)(b * HKV + 2 * j) * SK * DH * 2;
#pragma unroll 1
      for (int c = 0; c < PF_DIST; c++) {
        mbar_wait_sleep(bar_full + (PF_Q0 + (c * PF_QS) / 2) * 8);
        if (elect_one()) l2_prefetch((kv_is_k(c) ? gk : gv) + kv0 + (size_t)kv_block(c) * 16384, 16384);
      }
    } else if (wi == 3) {
      const uint8_t* wq0 = gwq + (size_t)b * (HQ * DH * 2) + j * 1024 + (lane & 3) * 128;
#pragma unroll
      for (int i = 0; i < 3; i++) prefetch_line(wq0 + (size_t)(192 + 16 * (i * 8 + (lane >> 2))) * (HQ * DH * 2));
      if ((lane & 15) < 14) {
        const uint8_t* xr = gx + (size_t)(b * SQ + j * 14 + (lane & 15)) * (DM * 2) + (4 + (lane >> 4)) * 128;
        prefetch_line(xr); prefetch_line(xr + 256);
        if (lane < 16) prefetch_line(xr + 512);
      }
      mbar_wait_sleep(bar_full + 2 * 8);
#pragma unroll
      for (int i = 0; i < 5; i++)
        if (i * 8 + (lane >> 2) < 36) prefetch_line(wq0 + 512 + (size_t)(16 * (i * 8 + (lane >> 2))) * (HQ * DH * 2));
      if (lane == 0) {
        const uint32_t e = *reinterpret_cast<volatile uint32_t*>(g_epoch + b);
        asm volatile("st.shared.u32 [%0], %1;" ::"r"(s_tag), "r"((0x0800u + e % 0x7000u) << 16) : "memory");
        mbar_arrive_pred(bar_tag, true);
      }
      __syncwarp();
      const int row0 = (b * HKV + 2 * j) * SK;
      const size_t kv0 = (size_t)(b * HKV + 2 * j) * SK * DH * 2;
      uint64_t pol;
      asm volatile("createpolicy.fractional.L2::evict_first.b64 %0, 1.0;" : "=l"(pol));
      int slot = 0, pf = PF_DIST, acc = 0;
#pragma unroll 1
      for (int c = 0; c < 32; c++) {
        mbar_wait_sleep(bar_empty + (30 + c + (c >= 4)) * 8);
        const uint32_t f = bar_full + (FILL_KV0 + c) * 8;
        acc += (c >= PF_LAG) ? 32 - PF_DIST : 0;
        const bool dopf = acc >= PF_SPAN && pf < 32;
        if (elect_one()) {
          mbar_expect_tx(f, SLOT_BYTES);
          tma_3d(slots + slot * SLOT_BYTES, kv_is_k(c) ? &tm_k : &tm_v, 0, row0 + kv_block(c) * 64, 0, f, pol);
          if (dopf) l2_prefetch((kv_is_k(pf) ? gk : gv) + kv0 + (size_t)kv_block(pf) * 16384, 16384);
          if (c >= 29) l2_prefetch(gwo + (size_t)j * (512 * DM * 2) + (size_t)b * 36864 + (c - 29) * 12288, 12288);
        }
        if (dopf) { pf++; acc -= PF_SPAN; }
        slot = kv_next(slot);
      }
    }
  } else {
    asm volatile("setmaxnreg.inc.sync.aligned.u32 232;");
    const uint32_t peer_empty = mapa(bar_empty, rank ^ 1);
    const uint32_t dsb = (sb & 0x3FFFF) >> 4, dslots = dsb + OFF_SLOTS / 16;
    constexpr uint32_t BLK16 = BLK / 16, SLOT16 = SLOT_BYTES / 16;
    auto release_both = [&](int n) { mbar_arrive_pred(bar_empty + n * 8, lane == 0); mbar_arrive_remote_pred(peer_empty + n * 8, lane == 0); };
    auto release_kv = [&](int n) {
      mbar_arrive_pred(bar_empty + n * 8, lane == 0);
      mbar_arrive_remote_pred(peer_empty + n * 8, lane == 0 && n >= FILL_O0 - 5);
    };
    const uint32_t qblk = sb + (2 * wg) * BLK, dq = dsb + (2 * wg) * BLK16;
    float S[56];
    {
      float acc0[56], acc1[56];
      uint32_t q0[28], q1[28];
      if (wg == 1) named_arrive(4, 256);
      uint32_t qs = dslots + wg * SLOT16;
      auto q_step = [&](int n, int k) {
        const uint64_t da = mkdesc(qs), db = mkdesc(dsb + (k < 8 ? k * BLK16 : OFF_STAGE / 16));
        mbar_wait(bar_full + n * 8);
        named_bar(4 + wg, 256);
        WG_FENCE();
#pragma unroll
        for (int kk = 0; kk < 4; kk++) {
          wgmma_n112_ta(acc0, da + kk * 128, db + kk * 2, (k | kk) != 0);
          wgmma_n112_ta(acc1, da + (512 + kk * 128), db + kk * 2, (k | kk) != 0);
        }
        WG_COMMIT();
        named_arrive(4 + (wg ^ 1), 256);
        qs = (qs >= dslots + 4 * SLOT16) ? qs - 4 * SLOT16 : qs + 2 * SLOT16;
        if (k > 0) { WG_WAIT(1); release_both(n - 2); }
      };
#pragma unroll 1
      for (int k = 0; k < 9; k++) {
        mbar_wait(bar_x + k * 8);
        q_step(k * 2 + wg, k);
      }
      WG_WAIT(0);
      release_both(16 + wg);
      pin(acc0); pin(acc1);
      pack_tile_scaled(q0, acc0); pack_tile_scaled(q1, acc1);
#pragma unroll 1
      for (int k = 0; k < 9; k++) {
        q_step(18 + k * 2 + wg, k);
        if (k == 4 + wg) store_tile_t<0, 4>(qblk, q0, wi, lane);
        if (k == 5 + wg) store_tile_t<4, 7>(qblk, q0, wi, lane);
        if (k == 6 + wg) store_tile_t<0, 4>(qblk + BLK, q1, wi, lane);
        if (k == 7 + wg) store_tile_t<4, 7>(qblk + BLK, q1, wi, lane);
      }
      WG_WAIT(0);
      if (wg == 1) release_both(35);
      if ((tid & 127) == 0) asm volatile("st.shared.u32 [%0], %1;" ::"r"(s_tag + 4 + 4 * wg), "r"(0xffffu) : "memory");
      fence_async_smem();
      mbar_wait(bar_full + FILL_KV0 * 8);
      named_bar(4 + wg, 256);
      WG_FENCE();
      issue_s(S, dslots, dq);
      WG_COMMIT();
      named_arrive(4 + (wg ^ 1), 256);
      sched_fence(zero);
      pin(acc0); pin(acc1);
      pack_tile_scaled(q0, acc0); pack_tile_scaled(q1, acc1);
      store_tile_t(qblk + 4 * BLK, q0, wi, lane);
      store_tile_t(qblk + 5 * BLK, q1, wi, lane);
      WG_WAIT(0);
    }
    {
      float O0[56], O1[56], l[28];
#pragma unroll
      for (int i = 0; i < 28; i++) l[i] = 0.f;
      const uint32_t pbuf = wg ? stage : slots + 4 * SLOT_BYTES, dp = (pbuf & 0x3FFFF) >> 4, aux = sb + OFF_AUX + wg * 896;
      int ks = 1, vs = 2;
      bool sub = false;
      const uint32_t flag = s_tag + 4 + 4 * wg;
      auto failed = [&](int jj) {
        uint32_t f;
        asm volatile("ld.shared.u32 %0, [%1];" : "=r"(f) : "r"(flag) : "memory");
        return f == (uint32_t)jj;
      };
      auto redo = [&](int jj) {
        pin(O0); pin(O1);
        redo_block(S, O0, O1, l, gk + ((size_t)(b * HKV + 2 * j) * SK + (jj - 1) * 64) * (DH * 2), dq + (jj > 8 ? 4 * BLK16 : 0), pbuf, aux,
                   2 + wg, (jj & 7) == 1, sub, zero);
        sub = true;
      };
      const uint32_t pst = stsm_t_base(pbuf, wi, lane);
      const uint32_t spo = __shfl_sync(0xffffffffu, ((tid & 127) >> 2) * 480 + (lane & 3) * 8, lane);
      auto report = [&](int jj, int mx) {
        asm volatile("{\n.reg .pred p;\nsetp.gt.s32 p, %2, %3;\n@p st.shared.u32 [%0], %1;\n}\n" ::"r"(flag), "r"(jj + 1), "r"(mx), "n"(L_HI_BITS) : "memory");
      };
      {
        pin(S);
        release_kv(FILL_KV0);
        int mx = underflows(S) ? 0x7fffffff : 0;
        uint32_t pk[28];
        exp_groups<0, 14>(S, pk, l, 1.f, mx);
        store_tile_at<0, 7>(pst, pk);
        mbar_wait(bar_full + (FILL_KV0 + 1) * 8);
        report(0, mx);
        fence_async_smem();
      }
#pragma unroll 1
      for (int jj = 1; jj < 16; jj++) {
        named_bar(4 + wg, 256);
        const bool fl = failed(jj);
        WG_FENCE();
        issue_s(S, dslots + ks * SLOT16, dq + (jj >= 8 ? 4 * BLK16 : 0));
        WG_COMMIT();
        if (__builtin_expect(__any_sync(0xffffffffu, fl), 0)) {
          WG_WAIT(0);
          pin(S);
          redo(jj);
          WG_FENCE();
          issue_s(S, dslots + ks * SLOT16 + zero, dq + (jj >= 8 ? 4 * BLK16 : 0) + zero);
          WG_COMMIT();
        }
        mbar_wait(bar_full + (FILL_KV0 + 2 * jj) * 8);
        WG_FENCE();
        issue_pv(O0, O1, dslots + vs * SLOT16, dp, (jj & 7) != 1);
        WG_COMMIT();
        named_arrive(4 + (wg ^ 1), 256);
        ks = kv_next(vs); vs = kv_next(ks);
        if (jj == 8) {
          spill_sums(l, qblk + spo);
          __syncwarp();
          mbar_arrive_pred(bar_sum + wg * 16, lane == 0);
          sub = false;
        }
        WG_WAIT(1);
        pin(S);
        release_kv(FILL_KV0 + 2 * jj - 1);
        int mx = 0;
        const float keep = jj == 8 ? 0.f : 1.f;
        if (__builtin_expect(jj == 8 || sub, 0)) {
          if (jj == 8) { if (underflows(S)) mx = 0x7fffffff; }
          else sub_ref(S, aux, zero);
        }
        uint32_t pk[28];
        exp_groups<0, XH>(S, pk, l, keep, mx);
        mbar_wait(bar_full + (FILL_KV0 + 2 * jj + 1) * 8);
        WG_WAIT(0);
        release_kv(FILL_KV0 + 2 * jj);
        store_tile_at<0, XH / 2>(pst, pk);
        exp_groups<XH, 14>(S, pk, l, keep, mx);
        store_tile_at<XH / 2, 7>(pst, pk);
        if (jj == 8) {
          float inv[28];
          mbar_wait(bar_sum + wg * 16 + 8);
          pin(O0); pin(O1);
          store_o(pst - pbuf + qblk, O0, O1, inv, aux + 448 + (spo & 24));
        }
        report(jj, mx);
        fence_async_smem();
      }
      named_bar(4 + wg, 256);
      if (__builtin_expect(__any_sync(0xffffffffu, failed(16)), 0)) redo(16);
      WG_FENCE();
      issue_pv(O0, O1, dslots + ks * SLOT16, dp, 1);
      WG_COMMIT();
      if (wg == 0) named_arrive(5, 256);
      sum_columns(l, qblk + 4 * BLK, aux, 2 + wg);
      WG_WAIT(0);
      pin(O0); pin(O1);
      release_kv(FILL_O0 - 1);
      if (wg == 0) release_both(34);
      named_bar(2 + wg, 128);
      store_o(pst - pbuf + qblk + 4 * BLK, O0, O1, l, aux + 448 + (spo & 24));
      fence_async_smem();
      if (wg == 1) named_arrive(1, 256);
      named_bar(2 + wg, 128);
    }
    {
      const int t128 = tid & 127;
      const uint4* pbase = g_part + (size_t)((b * 8 + j) * 8) * (8 * 128) + t128;
      const uint32_t xch = slots + wo_slot(30 % NSLOT) * SLOT_BYTES + t128 * 16;
      float sum[56];
      uint4 v[8], v2[8];
      uint32_t tagbits = 0;
#pragma unroll
      for (int i = 0; i < 8; i++) v[i] = v2[i] = make_uint4(0, 0, 0, 0);
#pragma unroll
      for (int i = 0; i < 56; i++) sum[i] = 0.f;
#pragma unroll
      for (int si = 0; si < 5; si++) {
        const int s = 2 * si + (wg & 1);
        if (s > 8) break;
        const int ksplit = (si == 0 || si == 4) ? 2 : 4;
        float acc[56];
        if (s == 8) { add_partial(sum, v, pbase + ((j - 4) & 7) * (8 * 128), tagbits); pin(sum); }
        if (s > 0) named_bar(4 + wg, 256);
#pragma unroll
        for (int kh = 0; kh < 2; kh++) {
          if (kh == 1 && s == 0) named_bar(1, 256);
          if (kh == 1 && s == 8) load_chunks(v, pbase + ((j - 7) & 7) * (8 * 128), 128);
#pragma unroll 1
          for (int kq = (kh ? ksplit : 0); kq < (kh ? 4 : ksplit); kq++) {
            const int n = FILL_O0 + s * 4 + kq;
            const uint64_t da = mkdesc(dslots + wo_slot((s * 4 + kq) % NSLOT) * SLOT16), db = mkdesc(dsb + (2 * o_quarter(kq)) * BLK16);
            mbar_wait(bar_full + n * 8);
            WG_FENCE();
#pragma unroll
            for (int kk = 0; kk < 8; kk++)
              wgmma_n112_ta(acc, da + kk * 128, db + ((kk >> 2) * BLK16 + (kk & 3) * 2), kk | kq);
            WG_COMMIT();
            if (kq == 3 && s < 8) named_arrive(4 + (wg ^ 1), 256);
            if (kq > 0) { WG_WAIT(1); if (n - 1 < NFILL - NSLOT) release_both(n - 1); }
          }
        }
        if (s < 2) {
          mbar_wait(bar_tag);
          asm volatile("ld.shared.u32 %0, [%1];" : "=r"(tagbits) : "r"(s_tag) : "memory");
        }
        if (s >= 5 && s < 8) add_partial(sum, v, pbase + ((j + 4 - s) & 7) * (8 * 128), tagbits);
        if (s >= 3 && s < 8) load_chunks(v, pbase + ((j + 2 - s) & 7) * (8 * 128), 128);
        if (s == 7) load_chunks(v2, pbase + ((j - 6) & 7) * (8 * 128), 128);
        pin(sum);
        if (s == 8) {
          named_bar(1, 256);
#pragma unroll
          for (int i = 0; i < 14; i++) {
            float4 t;
            asm volatile("ld.shared.v4.f32 {%0, %1, %2, %3}, [%4];" : "=f"(t.x), "=f"(t.y), "=f"(t.z), "=f"(t.w) : "r"(xch + i * 2048) : "memory");
            sum[4 * i] += t.x; sum[4 * i + 1] += t.y; sum[4 * i + 2] += t.z; sum[4 * i + 3] += t.w;
          }
          add_partial(sum, v, pbase + ((j - 7) & 7) * (8 * 128), tagbits);
          WG_WAIT(0);
          pin(acc);
#pragma unroll
          for (int i = 0; i < 56; i++) sum[i] += acc[i];
          uint32_t pk[28];
          pack_tile(pk, sum);
          const uint32_t stg = slots + wo_slot(32 % NSLOT) * SLOT_BYTES;
          store_tile_t(stg, pk, wi, opaque_tid() & 31);
          named_bar(2, 128);
          uint4* orow = reinterpret_cast<uint4*>(gout + (size_t)(b * SQ + (t128 >> 3)) * DM + j * 64) + (t128 & 7);
          const uint32_t src = stg + (t128 >> 3) * 128 + (((t128 & 7) ^ ((t128 >> 3) & 7)) << 4);
#pragma unroll
          for (int i = 0; i < 7; i++) {
            uint4 t;
            asm volatile("ld.shared.v4.u32 {%0, %1, %2, %3}, [%4];" : "=r"(t.x), "=r"(t.y), "=r"(t.z), "=r"(t.w) : "r"(src + i * 2048) : "memory");
            orow[(size_t)i * 16 * (DM / 8)] = t;
          }
          if (j == 0 && t128 == 0) atomicAdd(g_epoch + b, 1u);
        } else {
          WG_WAIT(0);
          pin(acc);
          if (FILL_O0 + s * 4 + 3 < NFILL - NSLOT) release_both(FILL_O0 + s * 4 + 3);
          const float tagf = __uint_as_float(tagbits);
          if (s < 7) {
            uint4* dst = g_part + (size_t)((b * 8 + o_tile_of_step(j, s)) * 8 + j) * (8 * 128) + t128;
#pragma unroll
            for (int i = 0; i < 8; i++) store_chunk(dst + i * 128, acc + 7 * i, tagf);
          } else {
            uint4* dst = g_part8 + (size_t)(((b * 8 + 2 * wi) * 8 + j) * 4) * 32 + lane;
#pragma unroll
            for (int h = 0; h < 2; h++) {
              float e[28];
#pragma unroll
              for (int i = 0; i < 28; i++) e[i] = acc[4 * (i >> 1) + 2 * h + (i & 1)];
#pragma unroll
              for (int c = 0; c < 4; c++) store_chunk(dst + (h * 8 * 4 + c) * 32, e + 7 * c, tagf);
            }
          }
        }
      }
      if (wg == 1) {
        const uint4* s8 = g_part8 + (size_t)(((b * 8 + j) * 8) * 4 + wi) * 32 + lane;
        add_partial(sum, v, pbase + ((j - 5) & 7) * (8 * 128), tagbits);
        add_partial(sum, v2, pbase + ((j - 6) & 7) * (8 * 128), tagbits);
        named_bar(3, 128);
#pragma unroll
        for (int i = 0; i < 14; i++)
          asm volatile("st.shared.v4.f32 [%0], {%1, %2, %3, %4};" ::"r"(xch + i * 2048), "f"(sum[4 * i]), "f"(sum[4 * i + 1]), "f"(sum[4 * i + 2]), "f"(sum[4 * i + 3]) : "memory");
        named_arrive(1, 256);
        load_chunks(v, s8, 4 * 32);
        check_chunks(v, s8, 4 * 32, tagbits);
        float r[7];
#pragma unroll
        for (int i = 0; i < 7; i++) r[i] = 0.f;
#pragma unroll
        for (int d = 0; d < 8; d++) add_chunk(r, v[d]);
        const int odd = wi & 1;
        __nv_bfloat16* dst = gout + (size_t)(b * SQ + 4 * (7 * wi - odd) + 2 * (lane & 3)) * DM + 512 + 8 * j + (lane >> 2);
        __nv_bfloat16* dA = dst + odd * DM;
        __nv_bfloat16* dB = dst + (1 + 7 * odd) * DM;
#pragma unroll
        for (int i = 0; i < 7; i++) ((i & 1) ? dB : dA)[(i >> 1) * 8 * DM] = __float2bfloat16(r[i]);
      }
    }
  }
}

typedef CUresult (*EncodeFn)(CUtensorMap*, CUtensorMapDataType, cuuint32_t, void*, const cuuint64_t*, const cuuint64_t*,
                             const cuuint32_t*, const cuuint32_t*, CUtensorMapInterleave, CUtensorMapSwizzle,
                             CUtensorMapL2promotion, CUtensorMapFloatOOBfill);

void make_map(EncodeFn enc, CUtensorMap* m, const void* ptr, int rank, const cuuint64_t* dims, const cuuint64_t* strides,
              const cuuint32_t* box) {
  cuuint32_t es[3] = {1, 1, 1};
  enc(m, CU_TENSOR_MAP_DATA_TYPE_BFLOAT16, rank, const_cast<void*>(ptr), dims, strides, box, es, CU_TENSOR_MAP_INTERLEAVE_NONE,
      CU_TENSOR_MAP_SWIZZLE_128B, CU_TENSOR_MAP_L2_PROMOTION_L2_128B, CU_TENSOR_MAP_FLOAT_OOB_FILL_NONE);
}

}

extern "C" void kernel_launch(void* const* d_in, const int* in_sizes, int n_in, void* d_out, int out_size) {
  (void)in_sizes; (void)n_in; (void)out_size;
  static EncodeFn enc = nullptr;
  if (!enc) {
    void* fn = nullptr;
    cudaDriverEntryPointQueryResult qr;
    cudaGetDriverEntryPoint("cuTensorMapEncodeTiled", &fn, cudaEnableDefault, &qr);
    enc = (EncodeFn)fn;
    cudaFuncSetAttribute(gqa_fused_kernel, cudaFuncAttributeMaxDynamicSharedMemorySize, SMEM_BYTES);
  }
  CUtensorMap tx, tk, tv, twq, two;
  {
    cuuint64_t d[2] = {DM, B_ * SQ}, s[1] = {DM * 2}; cuuint32_t bx[2] = {64, SQ};
    make_map(enc, &tx, d_in[0], 2, d, s, bx);
  }
  {
    cuuint64_t d[3] = {64, (cuuint64_t)B_ * HKV * SK, 2}, s[2] = {DH * 2, 128}; cuuint32_t bx[3] = {64, 64, 2};
    make_map(enc, &tk, d_in[1], 3, d, s, bx);
    make_map(enc, &tv, d_in[2], 3, d, s, bx);
  }
  {
    cuuint64_t d[2] = {HQ * DH, DM}, s[1] = {HQ * DH * 2}; cuuint32_t bx[2] = {64, 64};
    make_map(enc, &twq, d_in[3], 2, d, s, bx);
  }
  {
    cuuint64_t d[2] = {DM, HQ * DH}, s[1] = {DM * 2}; cuuint32_t bx[2] = {64, 64};
    make_map(enc, &two, d_in[4], 2, d, s, bx);
  }
  gqa_fused_kernel<<<128, NTHREADS, SMEM_BYTES>>>(tx, tk, tv, twq, two, (const uint8_t*)d_in[0], (const uint8_t*)d_in[1], (const uint8_t*)d_in[2],
                                                   (const uint8_t*)d_in[3], (const uint8_t*)d_in[4], (__nv_bfloat16*)d_out, 0);
}
```
